```python
import torch

def _softmax(x, axis=-1):
    return torch.softmax(x, dim=axis)
def _gelu(x):
    return torch.nn.functional.gelu(x, approximate="tanh")
def _silu(x):
    return torch.nn.functional.silu(x)
def _sigmoid(x):
    return torch.sigmoid(x)
def _layernorm(x, axis=-1, eps=1e-5):
    m = x.mean(dim=axis, keepdim=True)
    v = x.var(dim=axis, keepdim=True, unbiased=False)
    return (x - m) / torch.sqrt(v + eps)
def _scatter_add(tgt, idx, src, axis=0):
    return tgt.clone().index_add_(axis, idx, src)
def _segment_sum(src, seg, n):
    out = torch.zeros((n,) + src.shape[1:], dtype=src.dtype)
    return out.index_add_(0, seg, src)
def _pad(x, pw):
    flat = tuple(v for pair in reversed(pw) for v in pair)
    return torch.nn.functional.pad(x, flat)

kernel_name = 'parallel_sum__mha_block_cached__dense_activation_gelu__decode'

def setup_inputs():

    _w = (lambda a: (lambda t: t.to(torch.bfloat16) if t.is_floating_point() else t)(torch.as_tensor(a)))
    def _A_setup():
        B, Sq, D = 8, 1, 512
        H, Sk, Dh = 32, 4096, 128
        return {
            "x": _w((lambda *s: torch.randn(*s, dtype=torch.bfloat16) * 0.05)(B, Sq, D)),
            "k_cache": _w((lambda *s: torch.randn(*s, dtype=torch.bfloat16) * 3.2)(B, H, Sk, Dh)),
            "v_cache": _w((lambda *s: torch.randn(*s, dtype=torch.bfloat16) * 0.8)(B, H, Sk, Dh)),
            "wq": _w((lambda *s: torch.randn(*s, dtype=torch.bfloat16) * 3.2)(D, H * Dh) * (D ** -0.5)),
            "wo": _w((lambda *s: torch.randn(*s, dtype=torch.bfloat16) * 0.8)(H * Dh, D) * ((H * Dh) ** -0.5)),
        }
    _A_in = _A_setup()

    def _B_setup():
        B, S, D, F = 8, 1, 512, 1792
        return {
            "x": _w((lambda *s: torch.randn(*s, dtype=torch.bfloat16) * 0.05)(B, S, D)),
            "w1": _w((lambda *s: torch.randn(*s, dtype=torch.bfloat16) * 3.2)(D, F) * (D ** -0.5)),
            "b1": _w((lambda *s: torch.randn(*s, dtype=torch.bfloat16) * 3.2)(F) * 0.01),
            "w2": _w((lambda *s: torch.randn(*s, dtype=torch.bfloat16) * 0.4)(F, D) * (F ** -0.5)),
            "b2": _w((lambda *s: torch.randn(*s, dtype=torch.bfloat16) * 0.4)(D) * 0.01),
        }
    _B_in = _B_setup()

    return {
        "A_x": _A_in["x"],
        "A_k_cache": _A_in["k_cache"],
        "A_v_cache": _A_in["v_cache"],
        "A_wq": _A_in["wq"],
        "A_wo": _A_in["wo"],
        "B_x": _B_in["x"],
        "B_w1": _B_in["w1"],
        "B_b1": _B_in["b1"],
        "B_w2": _B_in["w2"],
        "B_b2": _B_in["b2"],
    }

def reference(A_x, A_k_cache, A_v_cache, A_wq, A_wo, B_x, B_w1, B_b1, B_w2, B_b2):
    def _A_ref(x, k_cache, v_cache, wq, wo):
        B, Sq, D = x.shape
        H, Dh = 32, 128
        q = (lambda x, *d: x.permute(*d))((x @ wq).reshape(B, Sq, H, Dh), 0, 2, 1, 3)
        scores = torch.einsum("bhqd,bhkd->bhqk", q, k_cache) * (Dh ** -0.5)
        p = _softmax(scores, axis=-1)
        o = torch.einsum("bhqk,bhkd->bhqd", p, v_cache)
        return (lambda x, *d: x.permute(*d))(o, 0, 2, 1, 3).reshape(B, Sq, H * Dh) @ wo

    def _B_ref(x, w1, b1, w2, b2):
        h = torch.einsum("bsd,df->bsf", x, w1) + b1
        h = _gelu(h)
        return torch.einsum("bsf,fd->bsd", h, w2) + b2

    x = A_x
    xn = _layernorm(x, axis=-1)
    return x + _A_ref(xn, A_k_cache, A_v_cache, A_wq, A_wo) + _B_ref(xn, B_w1, B_b1, B_w2, B_b2)
```

```cpp
#include <cuda_runtime.h>
#include <cuda.h>
#include <cuda_bf16.h>
#include <stdint.h>
#include <limits.h>

namespace {

constexpr int kB = 8, kD = 512, kH = 32, kSK = 4096, kDH = 128, kF = 1792;
constexpr int kPairs = kB * kH;
constexpr int kTileKeys = 128;
constexpr int kTilesPerPair = kSK / kTileKeys;
constexpr int kTileBytes = kTileKeys * kDH * 2;
constexpr int kAuxBytes = 2048;
constexpr int kSlotBytes = kTileBytes + kAuxBytes;
constexpr int kSlots = 6;
constexpr int kLag = 32;
constexpr int kStreamUnits = 2 * kPairs * kTilesPerPair;
constexpr int kFSlices = kF / 128;
constexpr int kSlices = kH + kFSlices;
constexpr int kAttnUnits = kH * 4;
constexpr int kFfnUnits = kFSlices * 4;
constexpr int kQTasks = (kH * kDH) / 32;
constexpr int kFTasks = kF / 16;
constexpr int kFinalTasks = kB * kD / 32;
#define KWIN 6
#define KEARLY 6
#define NO_WQ_GATE
constexpr int kPieceBytes = kTileBytes / 4;
constexpr int kWin = KWIN;
constexpr int kStatic = kSlots - 1;
constexpr int kFfnPos = 2048;
constexpr int kTickets = kStreamUnits + kFfnUnits;
constexpr int kInStride = 272;
constexpr int kConsumerThreads = 128;
constexpr int kThreads = 160;
constexpr int kXnStride = 1040;
constexpr int kDoneCopies = 16;

constexpr uint32_t kTypeK = 0, kTypeV = 1, kTypeP = 2, kTypeSignal = 3, kTypeF = 4;
constexpr uint32_t kDescNoAux = 1u << 16;
static_assert(kStatic * 160 <= kLag * kTilesPerPair, "static units must be K units");
static_assert(kStatic * 160 <= kFfnPos, "static units precede the FFN units");

constexpr int kMiscOff = kSlots * kSlotBytes;
constexpr int kOffFull = kMiscOff;
constexpr int kOffEmpty = kOffFull + 256;
constexpr int kOffDesc = kOffEmpty + 64;
constexpr int kOffEpochBar = kOffDesc + 32;
constexpr int kOffEpoch = kOffDesc + 40;
constexpr int kOffGoBar = kOffDesc + 48;
constexpr int kOffL = kOffDesc + 64;
constexpr int kOffRed = kOffL + 64;
constexpr int kOffFin = kOffRed + 4096;
constexpr int kOffStamp = kOffFin + 1024;
constexpr int kOffXn = kOffStamp + 128;
constexpr int kOffPart = kOffXn + kB * kXnStride;
constexpr int kSmemUsed = kOffPart + 4096;
constexpr int kSmemBytes = kSmemUsed + 1024;
static_assert(kSmemBytes <= 232448, "shared memory budget");
static_assert(kSlots * 4 * 8 <= 256, "barrier area");

constexpr unsigned kSpinLimit = 1u << 26;

struct State {
    unsigned long long ticket;
    unsigned pad0[30];
    unsigned done[kDoneCopies][32];
};

__device__ __align__(128) State g_state;
__device__ __align__(128) uint2 g_q[kPairs * 64];
__device__ __align__(128) uint2 g_h[kB * (kF / 2)];
__device__ __align__(128) uint32_t g_score[kPairs * kSK];
__device__ __align__(128) uint32_t g_max[kPairs * 128];
__device__ __align__(128) float g_oacc[kPairs * kDH];
__device__ __align__(128) float g_lacc[kPairs * 32];
__device__ __align__(128) uint2 g_contrib[kSlices * kB * kD];

#define STAMP(i) do { } while (0)

__device__ __forceinline__ uint32_t smem_u32(const void* p) { return (uint32_t)__cvta_generic_to_shared(p); }

__device__ __forceinline__ void mbar_init(uint32_t bar, uint32_t cnt) {
    asm volatile("mbarrier.init.shared::cta.b64 [%0], %1;" ::"r"(bar), "r"(cnt) : "memory");
}
__device__ __forceinline__ void mbar_expect_tx(uint32_t bar, uint32_t bytes) {
    asm volatile("mbarrier.arrive.expect_tx.shared::cta.b64 _, [%0], %1;" ::"r"(bar), "r"(bytes) : "memory");
}
__device__ __forceinline__ void mbar_arrive(uint32_t bar) {
    asm volatile("mbarrier.arrive.shared::cta.b64 _, [%0];" ::"r"(bar) : "memory");
}
__device__ __forceinline__ bool mbar_try(uint32_t bar, uint32_t parity) {
    uint32_t ok;
    asm volatile(
        "{\n.reg .pred p;\n"
        "mbarrier.try_wait.parity.shared::cta.b64 p, [%1], %2;\n"
        "selp.u32 %0, 1, 0, p;\n}"
        : "=r"(ok) : "r"(bar), "r"(parity) : "memory");
    return ok != 0;
}
__device__ __forceinline__ void mbar_wait(uint32_t bar, uint32_t parity) {
    unsigned n = 0;
    while (!mbar_try(bar, parity)) {
        if (++n > kSpinLimit) __trap();
    }
}
__device__ __forceinline__ void bulk_load(uint32_t dst, const void* src, uint32_t bytes, uint32_t bar) {
    asm volatile("cp.async.bulk.shared::cluster.global.mbarrier::complete_tx::bytes [%0], [%1], %2, [%3];"
                 ::"r"(dst), "l"(src), "r"(bytes), "r"(bar) : "memory");
}
__device__ __forceinline__ void bulk_load_hint(uint32_t dst, const void* src, uint32_t bytes, uint32_t bar, uint64_t pol) {
    asm volatile("cp.async.bulk.shared::cluster.global.mbarrier::complete_tx::bytes.L2::cache_hint [%0], [%1], %2, [%3], %4;"
                 ::"r"(dst), "l"(src), "r"(bytes), "r"(bar), "l"(pol) : "memory");
}
__device__ __forceinline__ void tma_load_2d(uint32_t dst, const CUtensorMap* map, int c0, int c1, uint32_t bar) {
    asm volatile("cp.async.bulk.tensor.2d.shared::cluster.global.mbarrier::complete_tx::bytes [%0], [%1, {%3, %4}], [%2];"
                 ::"r"(dst), "l"(map), "r"(bar), "r"(c0), "r"(c1) : "memory");
}
__device__ __forceinline__ void tma_prefetch_2d(const CUtensorMap* map, int c0, int c1) {
    asm volatile("cp.async.bulk.prefetch.tensor.2d.L2.global.tile [%0, {%1, %2}];" ::"l"(map), "r"(c0), "r"(c1) : "memory");
}
__device__ __forceinline__ void cp_async16(uint32_t dst, const void* src) {
    asm volatile("cp.async.cg.shared.global [%0], [%1], 16;" ::"r"(dst), "l"(src) : "memory");
}
__device__ __forceinline__ void cp_async16_pf(uint32_t dst, const void* src) {
    asm volatile("cp.async.cg.shared.global.L2::256B [%0], [%1], 16;" ::"r"(dst), "l"(src) : "memory");
}
__device__ __forceinline__ void cp_async_commit() { asm volatile("cp.async.commit_group;" ::: "memory"); }
template <int N>
__device__ __forceinline__ void cp_async_wait() { asm volatile("cp.async.wait_group %0;" ::"n"(N) : "memory"); }

__device__ __forceinline__ void named_bar(int id, int n) { asm volatile("bar.sync %0, %1;" ::"r"(id), "r"(n) : "memory"); }

__device__ __forceinline__ void ldsm4(uint32_t (&r)[4], uint32_t addr) {
    asm volatile("ldmatrix.sync.aligned.m8n8.x4.shared.b16 {%0,%1,%2,%3}, [%4];"
                 : "=r"(r[0]), "=r"(r[1]), "=r"(r[2]), "=r"(r[3]) : "r"(addr) : "memory");
}
__device__ __forceinline__ void ldsm4t(uint32_t (&r)[4], uint32_t addr) {
    asm volatile("ldmatrix.sync.aligned.m8n8.x4.trans.shared.b16 {%0,%1,%2,%3}, [%4];"
                 : "=r"(r[0]), "=r"(r[1]), "=r"(r[2]), "=r"(r[3]) : "r"(addr) : "memory");
}
__device__ __forceinline__ void mma16816(float (&c)[4], const uint32_t (&a)[4], uint32_t b0, uint32_t b1) {
    asm volatile("mma.sync.aligned.m16n8k16.row.col.f32.bf16.bf16.f32 {%0,%1,%2,%3}, {%4,%5,%6,%7}, {%8,%9}, {%0,%1,%2,%3};"
                 : "+f"(c[0]), "+f"(c[1]), "+f"(c[2]), "+f"(c[3])
                 : "r"(a[0]), "r"(a[1]), "r"(a[2]), "r"(a[3]), "r"(b0), "r"(b1));
}
__device__ __forceinline__ uint32_t lds32(uint32_t a) { uint32_t v; asm volatile("ld.shared.u32 %0, [%1];" : "=r"(v) : "r"(a) : "memory"); return v; }
__device__ __forceinline__ uint2 lds64(uint32_t a) { uint2 v; asm volatile("ld.shared.v2.u32 {%0,%1}, [%2];" : "=r"(v.x), "=r"(v.y) : "r"(a) : "memory"); return v; }
__device__ __forceinline__ uint4 lds128(uint32_t a) { uint4 v; asm volatile("ld.shared.v4.u32 {%0,%1,%2,%3}, [%4];" : "=r"(v.x), "=r"(v.y), "=r"(v.z), "=r"(v.w) : "r"(a) : "memory"); return v; }
__device__ __forceinline__ float lds_f(uint32_t a) { float v; asm volatile("ld.shared.f32 %0, [%1];" : "=f"(v) : "r"(a) : "memory"); return v; }
__device__ __forceinline__ void sts32(uint32_t a, uint32_t v) { asm volatile("st.shared.u32 [%0], %1;" ::"r"(a), "r"(v) : "memory"); }
__device__ __forceinline__ void sts_f(uint32_t a, float v) { asm volatile("st.shared.f32 [%0], %1;" ::"r"(a), "f"(v) : "memory"); }
__device__ __forceinline__ void sts128(uint32_t a, uint4 v) { asm volatile("st.shared.v4.u32 [%0], {%1,%2,%3,%4};" ::"r"(a), "r"(v.x), "r"(v.y), "r"(v.z), "r"(v.w) : "memory"); }

__device__ __forceinline__ uint2 ld_rlx64(const uint2* p) {
    unsigned long long v;
    asm volatile("ld.relaxed.gpu.global.b64 %0, [%1];" : "=l"(v) : "l"(p) : "memory");
    return make_uint2((uint32_t)v, (uint32_t)(v >> 32));
}
__device__ __forceinline__ void st_rlx64(uint2* p, uint32_t lo, uint32_t hi) {
    unsigned long long v = ((unsigned long long)hi << 32) | lo;
    asm volatile("st.relaxed.gpu.global.b64 [%0], %1;" ::"l"(p), "l"(v) : "memory");
}
__device__ __forceinline__ uint4 ld_rlx128(const uint32_t* p) {
    uint4 v;
    asm volatile("ld.relaxed.gpu.global.v4.u32 {%0,%1,%2,%3}, [%4];" : "=r"(v.x), "=r"(v.y), "=r"(v.z), "=r"(v.w) : "l"(p) : "memory");
    return v;
}
__device__ __forceinline__ void st_rlx128(uint32_t* p, uint4 v) {
    asm volatile("st.relaxed.gpu.global.v4.u32 [%0], {%1,%2,%3,%4};" ::"l"(p), "r"(v.x), "r"(v.y), "r"(v.z), "r"(v.w) : "memory");
}
__device__ __forceinline__ void st_rlx32(uint32_t* p, uint32_t v) {
    asm volatile("st.relaxed.gpu.global.u32 [%0], %1;" ::"l"(p), "r"(v) : "memory");
}
__device__ __forceinline__ uint32_t ld_rlx32(const uint32_t* p) {
    uint32_t v;
    asm volatile("ld.relaxed.gpu.global.u32 %0, [%1];" : "=r"(v) : "l"(p) : "memory");
    return v;
}
__device__ __forceinline__ uint32_t ld_acq32(const uint32_t* p) {
    uint32_t v;
    asm volatile("ld.acquire.gpu.global.u32 %0, [%1];" : "=r"(v) : "l"(p) : "memory");
    return v;
}
__device__ __forceinline__ float4 ld_rlx_f4(const float* p) {
    float4 v;
    asm volatile("ld.relaxed.gpu.global.v4.f32 {%0,%1,%2,%3}, [%4];" : "=f"(v.x), "=f"(v.y), "=f"(v.z), "=f"(v.w) : "l"(p) : "memory");
    return v;
}
__device__ __forceinline__ uint32_t ldg_u32(const void* p) { uint32_t v; asm volatile("ld.global.nc.u32 %0, [%1];" : "=r"(v) : "l"(p)); return v; }
__device__ __forceinline__ uint32_t ldg_u16(const void* p) { uint16_t v; asm volatile("ld.global.nc.u16 %0, [%1];" : "=h"(v) : "l"(p)); return v; }
__device__ __forceinline__ void prefetch_l2(const void* p) { asm volatile("prefetch.global.L2 [%0];" ::"l"(p)); }
__device__ __forceinline__ float2 ld_rlx_f2(const float* p) {
    float2 v;
    asm volatile("ld.relaxed.gpu.global.v2.f32 {%0,%1}, [%2];" : "=f"(v.x), "=f"(v.y) : "l"(p) : "memory");
    return v;
}
__device__ __forceinline__ float ld_rlx_f(const float* p) {
    float v;
    asm volatile("ld.relaxed.gpu.global.f32 %0, [%1];" : "=f"(v) : "l"(p) : "memory");
    return v;
}
__device__ __forceinline__ void red_add_f32(float* p, float v) {
    asm volatile("red.relaxed.gpu.global.add.f32 [%0], %1;" ::"l"(p), "f"(v) : "memory");
}
__device__ __forceinline__ void red_add_u32(unsigned* p, unsigned v) {
    asm volatile("red.relaxed.gpu.global.add.u32 [%0], %1;" ::"l"(p), "r"(v) : "memory");
}

__device__ __forceinline__ float bfr(float f) { return __bfloat162float(__float2bfloat16_rn(f)); }
__device__ __forceinline__ uint32_t bf_bits(float f) { return (uint32_t)__bfloat16_as_ushort(__float2bfloat16_rn(f)); }
__device__ __forceinline__ uint32_t pack_bf2(float lo, float hi) {
    __nv_bfloat162 v = __floats2bfloat162_rn(lo, hi);
    return *reinterpret_cast<uint32_t*>(&v);
}
__device__ __forceinline__ float bf_lo(uint32_t w) { return __uint_as_float(w << 16); }
__device__ __forceinline__ float bf_hi(uint32_t w) { return __uint_as_float(w & 0xffff0000u); }
__device__ __forceinline__ int ord(uint32_t bits) { int i = (int)bits; return i ^ ((i >> 31) & 0x7fffffff); }
__device__ __forceinline__ float ex2(float x) { float y; asm("ex2.approx.ftz.f32 %0, %1;" : "=f"(y) : "f"(x)); return y; }

__device__ __forceinline__ void decode_unit(uint32_t u, uint32_t& type, uint32_t& pair, uint32_t& tile) {
    const uint32_t blk = u >> 5;
    tile = u & 31;
    if (blk < (uint32_t)kLag) {
        type = kTypeK; pair = blk;
    } else if (blk < (uint32_t)(2 * kPairs - kLag)) {
        const uint32_t g = blk - kLag;
        if (g & 1) { type = kTypeK; pair = kLag + (g >> 1); }
        else       { type = kTypeV; pair = g >> 1; }
    } else {
        type = kTypeV; pair = blk - kPairs;
    }
}

__global__ void __launch_bounds__(kThreads, 1)
fused_decode_kernel(const __nv_bfloat16* __restrict__ x, const __nv_bfloat16* __restrict__ kc,
                    const __nv_bfloat16* __restrict__ vc, const __nv_bfloat16* __restrict__ wq,
                    const __nv_bfloat16* __restrict__ w1, const __nv_bfloat16* __restrict__ b1,
                    const __nv_bfloat16* __restrict__ b2, __nv_bfloat16* __restrict__ out,
                    const __grid_constant__ CUtensorMap map_wo, const __grid_constant__ CUtensorMap map_w2) {
    extern __shared__ uint8_t smem_raw[];
    const uint32_t sbase = (smem_u32(smem_raw) + 1023u) & ~1023u;
    const int tid = threadIdx.x;
    const int warp = tid >> 5;
    const int lane = tid & 31;
    const uint32_t G = gridDim.x;
    const uint32_t cta = blockIdx.x;

    if (warp == 4) {
        uint64_t pol;
        asm volatile("createpolicy.fractional.L2::evict_first.b64 %0, 1.0;" : "=l"(pol));
        uint32_t slot = 1, phase = 0;
        int tc = 4 - kWin;
        uint32_t tb = (uint32_t)((4 - kWin + 4 * kSlots) % (4 * kSlots)), tphase = 0;
        bool windowed = false;
        auto window = [&]() {
            if (windowed && tc >= 4) mbar_wait(sbase + kOffFull + tb * 8, tphase);
            ++tc;
            if (++tb == 4u * kSlots) { tb = 0; if (tc > 0) tphase ^= 1; }
        };
        auto wait_empty = [&]() { mbar_wait(sbase + kOffEmpty + slot * 8, phase ^ 1); };
        auto advance = [&]() { if (++slot == (uint32_t)kSlots) { slot = 0; phase ^= 1; } };
        auto issue_piece = [&](uint32_t type, uint32_t pair, uint32_t tile, int p, bool early) {
            window();
            if (lane == 0) {
                const uint32_t full = sbase + kOffFull + (slot * 4 + p) * 8;
                const uint32_t dst = sbase + slot * kSlotBytes;
                const size_t off = ((size_t)pair * kSK + (size_t)tile * kTileKeys + p * 32) * kDH;
                const __nv_bfloat16* src = (type == kTypeK ? kc : vc) + off;
                if (p == 0) {
                    sts32(sbase + kOffDesc + slot * 4, type | (pair << 3) | (tile << 11) | (early ? kDescNoAux : 0u));
                    if (early) {
                        mbar_expect_tx(full, kPieceBytes);
                    } else if (type == kTypeK) {
                        mbar_expect_tx(full, kPieceBytes + 512);
                        bulk_load(dst + kTileBytes, g_q + pair * 64, 512, full);
                    } else {
                        mbar_expect_tx(full, kPieceBytes + 1024);
                        bulk_load(dst + kTileBytes, g_score + pair * kSK + tile * kTileKeys, 512, full);
                        bulk_load(dst + kTileBytes + 512, g_max + pair * 128, 512, full);
                    }
                } else {
                    mbar_expect_tx(full, kPieceBytes);
                }
                bulk_load_hint(dst + p * kPieceBytes, src, kPieceBytes, full, pol);
            }
        };
        unsigned long long ticket = 0;
        if (lane == 0) {
            STAMP(0);
            for (int i = 0; i < kSlots * 4; i++) mbar_init(sbase + kOffFull + i * 8, 1);
            for (int i = 0; i < kSlots; i++) mbar_init(sbase + kOffEmpty + i * 8, 4);
            mbar_init(sbase + kOffEpochBar, 1);
            mbar_init(sbase + kOffGoBar, 1);
            asm volatile("fence.mbarrier_init.release.cluster;" ::: "memory");
            for (int i = 1; i < 4; i++) mbar_arrive(sbase + kOffFull + i * 8);
            ticket = atomicAdd(&g_state.ticket, 1ull);
        }
        named_bar(2, kThreads);
        for (int k = 0; k < kStatic; k++) {
            uint32_t type, pair, tile;
            decode_unit(cta + k * G, type, pair, tile);
            wait_empty();
#pragma unroll 1
            for (int p = 0; p < 4; p++) {
                if (k * 4 + p == KEARLY) {
                    windowed = true;
                }
                issue_piece(type, pair, tile, p, true);
                if (k * 4 + p == KEARLY - 1 && lane == 0) {
                    sts32(sbase + kOffEpoch, (uint32_t)(ticket >> 32));
                    mbar_arrive(sbase + kOffEpochBar);
                    asm volatile("prefetch.tensormap [%0];" ::"l"(&map_wo) : "memory");
                    asm volatile("prefetch.tensormap [%0];" ::"l"(&map_w2) : "memory");
                }
            }
            advance();
        }
        for (uint32_t ft = cta; ft < (uint32_t)kFTasks; ft += G) {
            wait_empty();
#pragma unroll 1
            for (int p = 0; p < 4; p++) {
                window();
                const uint32_t full = sbase + kOffFull + (slot * 4 + p) * 8;
                const __nv_bfloat16* src = w1 + ft * 16 + (size_t)(p * 128 + (lane >> 1)) * kF + (lane & 1) * 8;
                const uint32_t dst = sbase + slot * kSlotBytes + (p * 128 + (lane >> 1)) * 32 + (((lane & 1) ^ ((lane >> 3) & 1)) << 4);
#pragma unroll
                for (int i = 0; i < 8; i++) cp_async16_pf(dst + i * 512, src + (size_t)i * 16 * kF);
                asm volatile("cp.async.mbarrier.arrive.shared::cta.b64 [%0];" ::"r"(full) : "memory");
                __syncwarp();
                if (lane == 0) {
                    if (p == 0) sts32(sbase + kOffDesc + slot * 4, kTypeF | (ft << 3));
                    mbar_arrive(full);
                }
            }
            advance();
        }
        auto issue_proj = [&](uint32_t slice, uint32_t quarter, bool use_window) {
            const uint32_t dst = sbase + slot * kSlotBytes;
            wait_empty();
            const CUtensorMap* map = (slice < (uint32_t)kH) ? &map_wo : &map_w2;
            const int row = (int)((slice < (uint32_t)kH) ? slice : slice - kH) * 128;
            sts32(sbase + kOffDesc + slot * 4, kTypeP | (slice << 3) | (quarter << 11));
            for (int p = 0; p < 4; p++) {
                const uint32_t full = sbase + kOffFull + (slot * 4 + p) * 8;
                if (use_window) window();
                mbar_expect_tx(full, kPieceBytes);
                tma_load_2d(dst + p * kPieceBytes, map, (int)quarter * 128 + p * 32, row, full);
            }
            advance();
        };
        if (lane == 0) {
            uint32_t pending = (uint32_t)ticket;
            uint32_t u = pending + kStatic * G;
            while (u < (uint32_t)kTickets) {
                if (u >= (uint32_t)kFfnPos && u < (uint32_t)(kFfnPos + kFfnUnits)) {
                    pending = (uint32_t)atomicAdd(&g_state.ticket, 1ull);
                    const uint32_t f = u - kFfnPos;
                    issue_proj(kH + (f >> 2), f & 3, true);
                } else {
                    uint32_t type, pair, tile;
                    decode_unit(u < (uint32_t)kFfnPos ? u : u - kFfnUnits, type, pair, tile);
                    wait_empty();
                    issue_piece(type, pair, tile, 0, false);
                    pending = (uint32_t)atomicAdd(&g_state.ticket, 1ull);
#pragma unroll 1
                    for (int p = 1; p < 4; p++) issue_piece(type, pair, tile, p, false);
                    advance();
                }
                u = pending + kStatic * G;
            }
        }
        __syncwarp();
        if (cta < (uint32_t)kAttnUnits) {
            prefetch_l2(g_oacc + ((lane >> 2) * kH + (cta >> 2)) * kDH + (lane & 3) * 32);
            if (lane < 8) prefetch_l2(g_lacc + (lane * kH + (cta >> 2)) * 32);
        }
        for (uint32_t un = cta; un < (uint32_t)kAttnUnits; un += G) {
            uint2* cp = g_contrib + (size_t)(un >> 2) * (kB * kD) + (un & 3) * 128 + (lane >> 2) * kD + (lane & 3) * 2;
#pragma unroll 4
            for (int i = 0; i < 16; i++) st_rlx128(reinterpret_cast<uint32_t*>(cp + i * 8), make_uint4(0u, 0u, 0u, 0u));
        }
        __syncwarp();
        if (lane != 0) return;
        wait_empty();
        sts32(sbase + kOffDesc + slot * 4, kTypeSignal);
        for (int p = 0; p < 4; p++) mbar_arrive(sbase + kOffFull + (slot * 4 + p) * 8);
        advance();
        mbar_wait(sbase + kOffGoBar, 0);
        for (uint32_t a = cta; a < (uint32_t)kAttnUnits; a += G) issue_proj(a >> 2, a & 3, false);
        return;
    }

    const int g = lane >> 2;
    const int j = lane & 3;
    const int mi = lane >> 3;
    const int r = lane & 7;
    const bool diag = (j == (g >> 1));

    const uint32_t s_wq = sbase;
    const uint32_t s_xn = sbase + kOffXn;
    const uint32_t s_part = sbase + kOffPart;

    auto load_wq = [&](uint32_t task) {
        const __nv_bfloat16* src = wq + task * 32 + (size_t)(tid >> 2) * (kH * kDH) + (tid & 3) * 8;
        const uint32_t dst = s_wq + (tid >> 2) * 64 + (((tid & 3) ^ ((tid >> 3) & 3)) << 4);
#pragma unroll 4
        for (int i = 0; i < 16; i++) cp_async16_pf(dst + i * 2048, src + (size_t)i * 32 * (kH * kDH));
    };
#pragma unroll
    for (int i = 0; i < 4; i++) {
        const int row = warp * 2 + (i >> 1), ch = lane + (i & 1) * 32;
        cp_async16(s_xn + row * kXnStride + ch * 16, x + row * kD + ch * 8);
    }
    cp_async_commit();
    if (cta < (uint32_t)kQTasks) load_wq(cta);
    cp_async_commit();
    for (uint32_t qt = cta; qt < (uint32_t)kQTasks; qt += G)
        st_rlx64(g_q + ((tid >> 4) * kH + (qt >> 2)) * 64 + (qt & 3) * 16 + (tid & 15), 0u, 0u);
    uint32_t b1raw = 0, fxraw = 0, fb2raw = 0;
    if (tid < 64 && cta < (uint32_t)kFTasks) b1raw = ldg_u32(b1 + cta * 16 + 2 * (tid & 7));
    if (warp == 0 && cta < (uint32_t)kFinalTasks) {
        fxraw = ldg_u16(x + cta * 32 + lane);
        fb2raw = ldg_u16(b2 + ((cta * 32 + lane) & (kD - 1)));
    }
    named_bar(2, kThreads);
    if (tid == 0) STAMP(14);

    cp_async_wait<1>();
    __syncwarp();
    if (tid == 0) STAMP(10);
    {
        float v[2][16];
        float s[2], q2[2];
#pragma unroll
        for (int rr = 0; rr < 2; rr++) {
            const uint32_t a = s_xn + (warp * 2 + rr) * kXnStride + lane * 32;
            const uint4 x0 = lds128(a), x1 = lds128(a + 16);
            const uint32_t w[8] = {x0.x, x0.y, x0.z, x0.w, x1.x, x1.y, x1.z, x1.w};
#pragma unroll
            for (int i = 0; i < 8; i++) { v[rr][2 * i] = bf_lo(w[i]); v[rr][2 * i + 1] = bf_hi(w[i]); }
            float s0 = 0.f, s1 = 0.f, s2 = 0.f, s3 = 0.f;
#pragma unroll
            for (int i = 0; i < 4; i++) { s0 += v[rr][i]; s1 += v[rr][4 + i]; s2 += v[rr][8 + i]; s3 += v[rr][12 + i]; }
            s[rr] = (s0 + s1) + (s2 + s3);
        }
#pragma unroll
        for (int o = 16; o > 0; o >>= 1) {
            s[0] += __shfl_xor_sync(0xffffffffu, s[0], o);
            s[1] += __shfl_xor_sync(0xffffffffu, s[1], o);
        }
#pragma unroll
        for (int rr = 0; rr < 2; rr++) {
            const float mean = s[rr] * (1.0f / kD);
            s[rr] = mean;
            float t0 = 0.f, t1 = 0.f, t2 = 0.f, t3 = 0.f;
#pragma unroll
            for (int i = 0; i < 4; i++) {
                const float d0 = v[rr][i] - mean, d1 = v[rr][4 + i] - mean, d2 = v[rr][8 + i] - mean, d3 = v[rr][12 + i] - mean;
                t0 += d0 * d0; t1 += d1 * d1; t2 += d2 * d2; t3 += d3 * d3;
            }
            q2[rr] = (t0 + t1) + (t2 + t3);
        }
#pragma unroll
        for (int o = 16; o > 0; o >>= 1) {
            q2[0] += __shfl_xor_sync(0xffffffffu, q2[0], o);
            q2[1] += __shfl_xor_sync(0xffffffffu, q2[1], o);
        }
#pragma unroll
        for (int rr = 0; rr < 2; rr++) {
            const float mb = bfr(s[rr]);
            const float vb = bfr(q2[rr] * (1.0f / kD));
            const float sd = bfr(__fsqrt_rn(bfr(vb + 1e-5f)));
            const float rs = __frcp_rn(sd);
            uint32_t o[8];
#pragma unroll
            for (int i = 0; i < 8; i++) o[i] = pack_bf2(bfr(v[rr][2 * i] - mb) * rs, bfr(v[rr][2 * i + 1] - mb) * rs);
            const uint32_t a = s_xn + (warp * 2 + rr) * kXnStride + lane * 32;
            sts128(a, make_uint4(o[0], o[1], o[2], o[3]));
            sts128(a + 16, make_uint4(o[4], o[5], o[6], o[7]));
        }
    }

    uint32_t epoch = 0, tag32 = 0;
#pragma unroll 1
    for (uint32_t qt = cta; qt < (uint32_t)kQTasks; qt += G) {
        if (qt != cta) {
            named_bar(1, kConsumerThreads);
            load_wq(qt);
            cp_async_commit();
        }
        cp_async_wait<0>();
        named_bar(1, kConsumerThreads);
        if (tid == 0 && qt == cta) mbar_arrive(sbase + kOffFull + 0);
        float acc[2][2][4] = {};
        const uint32_t a0 = s_wq + (warp * 128 + (mi >> 1) * 8 + r) * 64 + (((mi & 1) ^ ((r >> 1) & 3)) << 4);
        const uint32_t b0 = s_xn + g * kXnStride + (warp * 128 + 2 * j) * 2;
#pragma unroll
        for (int ks = 0; ks < 8; ks++) {
            const uint32_t bx0 = lds32(b0 + ks * 32), bx1 = lds32(b0 + ks * 32 + 16);
#pragma unroll
            for (int mt = 0; mt < 2; mt++) {
                uint32_t a[4];
                ldsm4t(a, (a0 + ks * 1024) ^ (mt << 5));
                mma16816(acc[mt][ks & 1], a, bx0, bx1);
            }
        }
#pragma unroll
        for (int mt = 0; mt < 2; mt++) {
            const uint32_t p = s_part + (warp * 32 + mt * 16 + g) * 32 + j * 8;
            sts_f(p, acc[mt][0][0] + acc[mt][1][0]); sts_f(p + 4, acc[mt][0][1] + acc[mt][1][1]);
            sts_f(p + 256, acc[mt][0][2] + acc[mt][1][2]); sts_f(p + 260, acc[mt][0][3] + acc[mt][1][3]);
        }
        named_bar(1, kConsumerThreads);
        mbar_wait(sbase + kOffEpochBar, 0);
        tag32 = lds32(sbase + kOffEpoch) + 1;
        const int b = tid >> 4, cp = tid & 15;
        float v0 = 0.f, v1 = 0.f;
#pragma unroll
        for (int w = 0; w < 4; w++) {
            v0 += lds_f(s_part + (w * 32 + 2 * cp) * 32 + b * 4);
            v1 += lds_f(s_part + (w * 32 + 2 * cp + 1) * 32 + b * 4);
        }
        st_rlx64(g_q + (b * kH + (qt >> 2)) * 64 + (qt & 3) * 16 + cp, pack_bf2(v0, v1), tag32);
    }
    if (tid == 0 && cta >= (uint32_t)kQTasks) mbar_arrive(sbase + kOffFull + 0);
    if (tid == 0) STAMP(1);
    cp_async_wait<0>();
    asm volatile("fence.proxy.async.shared::cta;" ::: "memory");
    named_bar(1, kConsumerThreads);
    if (lane == 0) mbar_arrive(sbase + kOffEmpty + 0);
    mbar_wait(sbase + kOffEpochBar, 0);
    epoch = lds32(sbase + kOffEpoch);
    tag32 = epoch + 1;
    const uint32_t tag16 = (epoch % 65535u) + 1u;

    const uint32_t k_lane_off = (uint32_t)(warp * 32 + (mi & 1) * 8 + r) * 256u + (uint32_t)(((r & 6) | ((mi >> 1) ^ (r & 1))) << 4);
    const uint32_t v_lane_off = (uint32_t)(warp * 32 + (mi >> 1) * 8 + r) * 256u + (uint32_t)(((r & 6) | ((mi & 1) ^ (r & 1))) << 4);
    constexpr float kScale = 0.08838834764831845f;
    constexpr float kLog2e = 1.4426950408889634f;

    uint32_t slot = 1, phase = 0, rbuf = 0;
    float* const oacc = g_oacc;
    float* const lacc = g_lacc;
    auto stage_input = [&](uint32_t slice) {
        const int sb = tid >> 4, sc = tid & 15;
        uint4 inw;
        if (slice >= (uint32_t)kH) {
            const uint2* hp = g_h + sb * (kF / 2) + (slice - kH) * 64 + sc * 4;
            unsigned it = 0;
            bool ok;
            do {
                const uint2 w0 = ld_rlx64(hp), w1_ = ld_rlx64(hp + 1), w2_ = ld_rlx64(hp + 2), w3 = ld_rlx64(hp + 3);
                ok = (w0.y == tag32) && (w1_.y == tag32) && (w2_.y == tag32) && (w3.y == tag32);
                inw = make_uint4(w0.x, w1_.x, w2_.x, w3.x);
                if (++it > kSpinLimit) __trap();
            } while (!__all_sync(0xffffffffu, ok));
        } else {
            const float* op = g_oacc + (sb * kH + slice) * kDH + sc * 8;
            const float l = ld_rlx_f(g_lacc + (sb * kH + slice) * 32);
            const float4 v0 = ld_rlx_f4(op), v1 = ld_rlx_f4(op + 4);
            const float inv = __frcp_rn(l);
            inw = make_uint4(pack_bf2(v0.x * inv, v0.y * inv), pack_bf2(v0.z * inv, v0.w * inv),
                             pack_bf2(v1.x * inv, v1.y * inv), pack_bf2(v1.z * inv, v1.w * inv));
        }
        named_bar(1, kConsumerThreads);
        sts128(s_part + sb * kInStride + sc * 16, inw);
        named_bar(1, kConsumerThreads);
    };
    auto load_ffn = [&](uint32_t task) {
        const uint2* cp = g_contrib + (size_t)kH * (kB * kD) + task * 32 + lane;
        float sb = 0.f;
        if (warp == 0) return sb;
        unsigned it = 0;
        bool ok;
        do {
            ok = true;
            uint2 vb[5];
#pragma unroll
            for (int i = 0; i < 5; i++) {
                const int f = (warp - 1) * 5 + i;
                vb[i] = (f < kFSlices) ? ld_rlx64(cp + (size_t)f * (kB * kD)) : make_uint2(0u, tag32);
            }
            sb = 0.f;
#pragma unroll
            for (int i = 0; i < 5; i++) { ok = ok && (vb[i].y == tag32); sb += __uint_as_float(vb[i].x); }
            if (++it > kSpinLimit) __trap();
        } while (!__all_sync(0xffffffffu, ok));
        return sb;
    };
    float sum_ffn = 0.f;
    uint32_t attn_left = 0, attn_next = 0;
    bool staged = false;
    auto wait_unit = [&]() {
        mbar_wait(sbase + kOffFull + slot * 32, phase);
        if (warp != 0) mbar_wait(sbase + kOffFull + slot * 32 + warp * 8, phase);
    };

#pragma unroll 1
    while (true) {
        const uint32_t tile_base = sbase + slot * kSlotBytes;
        const uint32_t aux = tile_base + kTileBytes;
        const uint32_t empty_bar = sbase + kOffEmpty + slot * 8;
        wait_unit();
        const uint32_t desc = lds32(sbase + kOffDesc + slot * 4);
        if (++slot == (uint32_t)kSlots) { slot = 0; phase ^= 1; }
        const uint32_t type = desc & 7;

        if (type == kTypeK) {
            const uint32_t pair = (desc >> 3) & 255, tile = (desc >> 11) & 31;
            uint32_t qf[16];
            bool ok = !(desc & kDescNoAux);
#pragma unroll
            for (int t = 0; t < 8; t++) {
                const uint2 a = lds64(aux + ((((2 * t) ^ g) * 4 + j) << 3));
                const uint2 b = lds64(aux + ((((2 * t + 1) ^ g) * 4 + j) << 3));
                ok = ok && (a.y == tag32) && (b.y == tag32);
                qf[2 * t] = a.x; qf[2 * t + 1] = b.x;
            }
            if (!__all_sync(0xffffffffu, ok)) {
                named_bar(1, kConsumerThreads);
                if (tid < 64) {
                    unsigned n = 0;
                    const uint2* qp = g_q + pair * 64 + tid;
                    uint2 w = ld_rlx64(qp);
                    while (w.y != tag32) {
                        w = ld_rlx64(qp);
                        if (++n > kSpinLimit) __trap();
                    }
                    sts32(aux + tid * 8, w.x);
                    asm volatile("fence.proxy.async.shared::cta;" ::: "memory");
                }
                named_bar(1, kConsumerThreads);
#pragma unroll
                for (int t = 0; t < 8; t++) {
                    qf[2 * t] = lds32(aux + ((((2 * t) ^ g) * 4 + j) << 3));
                    qf[2 * t + 1] = lds32(aux + ((((2 * t + 1) ^ g) * 4 + j) << 3));
                }
            }
            float acc[2][2][4] = {};
#pragma unroll
            for (int mt = 0; mt < 2; mt++) {
                const uint32_t a0 = tile_base + k_lane_off + mt * 4096;
#pragma unroll
                for (int t = 0; t < 8; t++) {
                    uint32_t a[4];
                    ldsm4(a, a0 ^ (t << 5));
                    mma16816(acc[mt][t & 1], a, qf[2 * t], qf[2 * t + 1]);
                }
            }
            uint32_t wv[4];
            int mo = INT_MIN;
#pragma unroll
            for (int i = 0; i < 4; i++) {
                const int mt = i >> 1, hf = i & 1;
                const float c0 = acc[mt][0][hf * 2] + acc[mt][1][hf * 2];
                const float c1 = acc[mt][0][hf * 2 + 1] + acc[mt][1][hf * 2 + 1];
                const float c = (g & 1) ? c1 : c0;
                const uint32_t bits = __float_as_uint(bfr(bfr(c) * kScale));
                wv[i] = bits | tag16;
                mo = max(mo, ord(bits));
            }
            __syncwarp();
            if (lane == 0) mbar_arrive(empty_bar);
            mo = __reduce_max_sync(0xffffffffu, diag ? mo : INT_MIN);
            if (diag) st_rlx128(g_score + pair * kSK + tile * kTileKeys + warp * 32 + g * 4, make_uint4(wv[0], wv[1], wv[2], wv[3]));
            if (tile == 0 && warp == 0) {
                st_rlx128(reinterpret_cast<uint32_t*>(oacc + pair * kDH) + lane * 4, make_uint4(0u, 0u, 0u, 0u));
                st_rlx32(reinterpret_cast<uint32_t*>(lacc + pair * 32) + lane, 0u);
                asm volatile("fence.acq_rel.gpu;" ::: "memory");
            }
            if (lane == 0) st_rlx32(g_max + pair * 128 + tile * 4 + warp, ((uint32_t)ord((uint32_t)mo) & 0xffff0000u) | tag16);
        } else if (type == kTypeV) {
            const uint32_t pair = (desc >> 3) & 255, tile = (desc >> 11) & 31;
            uint4 sw = lds128(aux + (warp * 32 + g * 4) * 4);
            uint4 mw = lds128(aux + 512 + lane * 16);
            auto tags_ok = [&](const uint4& a) {
                return ((a.x & 0xffffu) == tag16) && ((a.y & 0xffffu) == tag16) && ((a.z & 0xffffu) == tag16) && ((a.w & 0xffffu) == tag16);
            };
            if (!__all_sync(0xffffffffu, tags_ok(sw) && tags_ok(mw))) {
                unsigned n = 0;
                do {
                    sw = ld_rlx128(g_score + pair * kSK + tile * kTileKeys + warp * 32 + g * 4);
                    mw = ld_rlx128(g_max + pair * 128 + lane * 4);
                    if (++n > kSpinLimit) __trap();
                } while (!__all_sync(0xffffffffu, tags_ok(sw) && tags_ok(mw)));
            }
            int mo = max(max(ord(mw.x & 0xffff0000u), ord(mw.y & 0xffff0000u)), max(ord(mw.z & 0xffff0000u), ord(mw.w & 0xffff0000u)));
            mo = __reduce_max_sync(0xffffffffu, mo);
            const float M = __uint_as_float((uint32_t)ord((uint32_t)mo));
            const uint32_t swv[4] = {sw.x, sw.y, sw.z, sw.w};
            uint32_t pb[4];
            float lsum = 0.f;
#pragma unroll
            for (int i = 0; i < 4; i++) {
                const float p = ex2((bf_hi(swv[i]) - M) * kLog2e);
                lsum += p;
                const uint32_t bits = bf_bits(p);
                pb[i] = diag ? ((g & 1) ? (bits << 16) : bits) : 0u;
            }
            lsum = diag ? lsum : 0.f;
            float acc[8][4] = {};
#pragma unroll
            for (int ks = 0; ks < 2; ks++) {
                const uint32_t a0 = tile_base + v_lane_off + ks * 4096;
#pragma unroll
                for (int t = 0; t < 8; t++) {
                    uint32_t a[4];
                    ldsm4t(a, a0 ^ (t << 5));
                    mma16816(acc[t], a, pb[2 * ks], pb[2 * ks + 1]);
                }
            }
            __syncwarp();
            if (lane == 0) mbar_arrive(empty_bar);
#pragma unroll
            for (int o = 16; o > 0; o >>= 1) lsum += __shfl_xor_sync(0xffffffffu, lsum, o);
            float U[16];
#pragma unroll
            for (int t = 0; t < 8; t++) { U[2 * t] = acc[t][0] + acc[t][3]; U[2 * t + 1] = acc[t][2] + acc[t][1]; }
            float W[8];
#pragma unroll
            for (int q = 0; q < 8; q++) {
                const int rr = (q & 1) | ((q >> 1) << 2);
                W[q] = U[rr] + __shfl_xor_sync(0xffffffffu, U[rr ^ 2], 1);
            }
            const uint32_t redb = sbase + kOffRed + rbuf * 2048 + warp * 512;
#pragma unroll
            for (int q = 0; q < 4; q++) {
                const int rr = (q & 1) | ((q >> 1) << 3);
                const int iw = (rr & 1) | ((rr >> 2) << 1);
                const int iw4 = ((rr ^ 4) & 1) | (((rr ^ 4) >> 2) << 1);
                const float X = W[iw] + __shfl_xor_sync(0xffffffffu, W[iw4], 2);
                sts_f(redb + (((rr ^ (2 * j)) * 8 + g) << 2), X);
            }
            if (lane == 0) sts_f(sbase + kOffL + rbuf * 16 + warp * 4, lsum);
            named_bar(1, kConsumerThreads);
            {
                const uint32_t rb = sbase + kOffRed + rbuf * 2048 + tid * 4;
                const float s = (lds_f(rb) + lds_f(rb + 512)) + (lds_f(rb + 1024) + lds_f(rb + 1536));
                red_add_f32(oacc + pair * kDH + tid, s);
                if (tid == 0) {
                    const uint32_t lb = sbase + kOffL + rbuf * 16;
                    red_add_f32(lacc + pair * 32, (lds_f(lb) + lds_f(lb + 4)) + (lds_f(lb + 8) + lds_f(lb + 12)));
                }
            }
            rbuf ^= 1;
        } else if (type == kTypeF) {
            const uint32_t ft = desc >> 3;
            float acc[4] = {};
            const uint32_t a0 = tile_base + (warp * 128 + (mi >> 1) * 8 + r) * 32 + (((mi & 1) ^ ((r >> 2) & 1)) << 4);
            const uint32_t b0 = s_xn + g * kXnStride + (warp * 128 + 2 * j) * 2;
#pragma unroll
            for (int ks = 0; ks < 8; ks++) {
                uint32_t a[4];
                ldsm4t(a, a0 + ks * 512);
                mma16816(acc, a, lds32(b0 + ks * 32), lds32(b0 + ks * 32 + 16));
            }
            __syncwarp();
            if (lane == 0) mbar_arrive(empty_bar);
            named_bar(1, kConsumerThreads);
            const uint32_t p = s_part + (warp * 16 + g) * 32 + j * 8;
            sts_f(p, acc[0]); sts_f(p + 4, acc[1]);
            sts_f(p + 256, acc[2]); sts_f(p + 260, acc[3]);
            named_bar(1, kConsumerThreads);
            if (tid < 64) {
                const int b = tid >> 3, cp = tid & 7;
                const uint32_t bw = (ft == cta) ? b1raw : ldg_u32(b1 + ft * 16 + 2 * cp);
                float v[2];
#pragma unroll
                for (int e = 0; e < 2; e++) {
                    float s = 0.f;
#pragma unroll
                    for (int w = 0; w < 4; w++) s += lds_f(s_part + (w * 16 + 2 * cp + e) * 32 + b * 4);
                    const float hh = bfr(bfr(s) + (e ? bf_hi(bw) : bf_lo(bw)));
                    const float inner = 0.7978845608028654f * (hh + 0.044715f * hh * hh * hh);
                    v[e] = 0.5f * hh * (1.0f + tanhf(inner));
                }
                st_rlx64(g_h + b * (kF / 2) + ft * 8 + cp, pack_bf2(v[0], v[1]), tag32);
            }
        } else if (type == kTypeP) {
            const uint32_t slice = (desc >> 3) & 255, quarter = (desc >> 11) & 3;
            if (tid == 0 && staged) STAMP(8);
            if (!staged) stage_input(slice);
            staged = false;
            uint32_t bf[8][2];
#pragma unroll
            for (int ks = 0; ks < 8; ks++) {
                const uint32_t a = s_part + g * kInStride + (ks * 16 + 2 * j) * 2;
                bf[ks][0] = lds32(a);
                bf[ks][1] = lds32(a + 16);
            }
            float acc[2][2][4] = {};
            const uint32_t a0 = tile_base + warp * kPieceBytes + ((mi >> 1) * 8 + r) * 64 + (((mi & 1) ^ ((r >> 1) & 3)) << 4);
#pragma unroll
            for (int ks = 0; ks < 8; ks++) {
#pragma unroll
                for (int mt = 0; mt < 2; mt++) {
                    uint32_t a[4];
                    ldsm4t(a, (a0 + ks * 1024) ^ (mt << 5));
                    mma16816(acc[mt][ks & 1], a, bf[ks][0], bf[ks][1]);
                }
            }
            uint2* cp = g_contrib + (size_t)slice * (kB * kD) + quarter * 128 + warp * 32 + g;
#pragma unroll
            for (int mt = 0; mt < 2; mt++) {
                st_rlx64(cp + (2 * j) * kD + mt * 16, __float_as_uint(acc[mt][0][0] + acc[mt][1][0]), tag32);
                st_rlx64(cp + (2 * j + 1) * kD + mt * 16, __float_as_uint(acc[mt][0][1] + acc[mt][1][1]), tag32);
                st_rlx64(cp + (2 * j) * kD + mt * 16 + 8, __float_as_uint(acc[mt][0][2] + acc[mt][1][2]), tag32);
                st_rlx64(cp + (2 * j + 1) * kD + mt * 16 + 8, __float_as_uint(acc[mt][0][3] + acc[mt][1][3]), tag32);
            }
            __syncwarp();
            if (lane == 0) mbar_arrive(empty_bar);
            if (attn_left > 0) {
                if (--attn_left == 0) break;
                attn_next += G;
                stage_input(attn_next >> 2);
                staged = true;
            }
        } else {
            __syncwarp();
            if (lane == 0) mbar_arrive(empty_bar);
            named_bar(1, kConsumerThreads);
            if (warp == 0) {
                if (tid == 0) STAMP(3);
                asm volatile("fence.acq_rel.gpu;" ::: "memory");
                if (tid == 0) STAMP(13);
                if (lane < kDoneCopies) red_add_u32(&g_state.done[lane][0], 1u);
                if (lane == 0) mbar_arrive(sbase + kOffGoBar);
            }
            if (cta < (uint32_t)kFinalTasks) sum_ffn = load_ffn(cta);
            for (uint32_t a = cta; a < (uint32_t)kAttnUnits; a += G) attn_left++;
            if (attn_left == 0) break;
            if (tid == 0) {
                const unsigned target = G * (epoch + 1);
                const unsigned* dp = &g_state.done[cta % kDoneCopies][0];
                unsigned it = 0;
                while ((int)(ld_acq32(dp) - target) < 0) {
                    if (++it > kSpinLimit) __trap();
                }
                STAMP(4);
                if (cta == 0) g_state.ticket = (unsigned long long)(epoch + 1) << 32;
            }
            named_bar(1, kConsumerThreads);
            attn_next = cta;
            stage_input(cta >> 2);
            staged = true;
            if (tid == 0) STAMP(9);
        }
    }
    if (tid == 0) STAMP(5);

#pragma unroll 1
    for (uint32_t task = cta; task < (uint32_t)kFinalTasks; task += G) {
        const uint32_t o = task * 32 + lane;
        if (task != cta) {
            named_bar(1, kConsumerThreads);
            if (warp == 0) {
                fxraw = ldg_u16(x + o);
                fb2raw = ldg_u16(b2 + (o & (kD - 1)));
            }
        }
        const float sb = (task == cta) ? sum_ffn : load_ffn(task);
        const uint2* cp = g_contrib + o;
        float sa;
        unsigned it = 0;
        bool ok;
        do {
            ok = true;
            uint2 va[8];
#pragma unroll
            for (int i = 0; i < 8; i++) va[i] = ld_rlx64(cp + (size_t)(warp * 8 + i) * (kB * kD));
            sa = 0.f;
#pragma unroll
            for (int i = 0; i < 8; i++) { ok = ok && (va[i].y == tag32); sa += __uint_as_float(va[i].x); }
            if (++it > kSpinLimit) __trap();
        } while (!__all_sync(0xffffffffu, ok));
        const uint32_t fb = sbase + kOffFin + warp * 256 + lane * 4;
        sts_f(fb, sa);
        sts_f(fb + 128, sb);
        named_bar(1, kConsumerThreads);
        if (warp == 0) {
            const uint32_t f0 = sbase + kOffFin + lane * 4;
            const float A = (lds_f(f0) + lds_f(f0 + 256)) + (lds_f(f0 + 512) + lds_f(f0 + 768));
            const float Bv = (lds_f(f0 + 128) + lds_f(f0 + 384)) + (lds_f(f0 + 640) + lds_f(f0 + 896));
            const float res = bfr(bf_lo(fxraw) + bfr(A)) + bfr(bfr(Bv) + bf_lo(fb2raw));
            out[o] = __float2bfloat16_rn(res);
        }
    }
}

}

typedef CUresult (*EncodeTiledFn)(CUtensorMap*, CUtensorMapDataType, cuuint32_t, void*, const cuuint64_t*, const cuuint64_t*,
                                  const cuuint32_t*, const cuuint32_t*, CUtensorMapInterleave, CUtensorMapSwizzle,
                                  CUtensorMapL2promotion, CUtensorMapFloatOOBfill);

static bool encode_weight_map(EncodeTiledFn fn, CUtensorMap* map, const void* base, int rows) {
    const cuuint64_t dims[2] = {(cuuint64_t)kD, (cuuint64_t)rows};
    const cuuint64_t strides[1] = {(cuuint64_t)kD * 2};
    const cuuint32_t box[2] = {32, 128};
    const cuuint32_t estr[2] = {1, 1};
    return fn(map, CU_TENSOR_MAP_DATA_TYPE_BFLOAT16, 2, const_cast<void*>(base), dims, strides, box, estr,
              CU_TENSOR_MAP_INTERLEAVE_NONE, CU_TENSOR_MAP_SWIZZLE_64B, CU_TENSOR_MAP_L2_PROMOTION_L2_256B,
              CU_TENSOR_MAP_FLOAT_OOB_FILL_NONE) == CUDA_SUCCESS;
}

extern "C" void kernel_launch(void* const* d_in, const int* in_sizes, int n_in, void* d_out, int out_size) {
    (void)in_sizes; (void)n_in; (void)out_size;
    const __nv_bfloat16* x  = (const __nv_bfloat16*)d_in[0];
    const __nv_bfloat16* kc = (const __nv_bfloat16*)d_in[1];
    const __nv_bfloat16* vc = (const __nv_bfloat16*)d_in[2];
    const __nv_bfloat16* wq = (const __nv_bfloat16*)d_in[3];
    const __nv_bfloat16* wo = (const __nv_bfloat16*)d_in[4];
    const __nv_bfloat16* w1 = (const __nv_bfloat16*)d_in[6];
    const __nv_bfloat16* b1 = (const __nv_bfloat16*)d_in[7];
    const __nv_bfloat16* w2 = (const __nv_bfloat16*)d_in[8];
    const __nv_bfloat16* b2 = (const __nv_bfloat16*)d_in[9];
    __nv_bfloat16* out = (__nv_bfloat16*)d_out;

    static int grid = 0;
    static EncodeTiledFn encode = nullptr;
    static CUtensorMap map_wo, map_w2;
    static const void* cached_wo = nullptr;
    static const void* cached_w2 = nullptr;
    if (grid == 0) {
        int dev = 0, sms = 0;
        cudaGetDevice(&dev);
        cudaDeviceGetAttribute(&sms, cudaDevAttrMultiProcessorCount, dev);
        cudaFuncSetAttribute(fused_decode_kernel, cudaFuncAttributeMaxDynamicSharedMemorySize, kSmemBytes);
        void* fn = nullptr;
        cudaDriverEntryPointQueryResult qres;
        cudaGetDriverEntryPoint("cuTensorMapEncodeTiled", &fn, cudaEnableDefault, &qres);
        encode = (EncodeTiledFn)fn;
        grid = sms > 0 ? sms : 1;
    }
    if (encode == nullptr) return;
    if (cached_wo != (const void*)wo) { encode_weight_map(encode, &map_wo, wo, kH * kDH); cached_wo = wo; }
    if (cached_w2 != (const void*)w2) { encode_weight_map(encode, &map_w2, w2, kF); cached_w2 = w2; }
    fused_decode_kernel<<<grid, kThreads, kSmemBytes>>>(x, kc, vc, wq, w1, b1, b2, out, map_wo, map_w2);
}
```

```cpp
#include <cuda_runtime.h>
#include <cuda.h>
#include <cuda_bf16.h>
#include <stdint.h>
#include <limits.h>

namespace {

constexpr int kB = 8, kD = 512, kH = 32, kSK = 4096, kDH = 128, kF = 1792;
constexpr int kPairs = kB * kH;
constexpr int kTileKeys = 128;
constexpr int kTilesPerPair = kSK / kTileKeys;
constexpr int kTileBytes = kTileKeys * kDH * 2;
constexpr int kAuxBytes = 2048;
constexpr int kSlotBytes = kTileBytes + kAuxBytes;
constexpr int kSlots = 6;
constexpr int kLag = 32;
constexpr int kStreamUnits = 2 * kPairs * kTilesPerPair;
constexpr int kFSlices = kF / 128;
constexpr int kSlices = kH + kFSlices;
constexpr int kAttnUnits = kH * 4;
constexpr int kFfnUnits = kFSlices * 4;
constexpr int kQTasks = (kH * kDH) / 32;
constexpr int kFTasks = kF / 16;
constexpr int kFinalTasks = kB * kD / 32;
#define KWIN 6
#define KEARLY 6
#define KFAST 2
constexpr int kPieceBytes = kTileBytes / 4;
constexpr int kWin = KWIN;
constexpr int kStatic = kSlots - 1;
#define FINAL_SLEEP 0
#define FFNPOS 2048
constexpr int kFfnPos = FFNPOS;
constexpr int kTickets = kStreamUnits + kFfnUnits;
constexpr int kInStride = 272;
constexpr int kConsumerThreads = 128;
constexpr int kThreads = 160;
constexpr int kXnStride = 1040;

constexpr uint32_t kTypeK = 0, kTypeV = 1, kTypeP = 2, kTypeSignal = 3, kTypeF = 4;
constexpr uint32_t kDescNoAux = 1u << 16;
static_assert(kStatic * 160 <= kLag * kTilesPerPair, "static units must be K units");
static_assert(kStatic * 160 <= kFfnPos, "static units precede the FFN units");

constexpr int kMiscOff = kSlots * kSlotBytes;
constexpr int kOffFull = kMiscOff;
constexpr int kOffEmpty = kOffFull + 256;
constexpr int kOffDesc = kOffEmpty + 64;
constexpr int kOffEpochBar = kOffDesc + 32;
constexpr int kOffEpoch = kOffDesc + 40;
constexpr int kOffL = kOffDesc + 64;
constexpr int kOffRed = kOffL + 64;
constexpr int kOffStamp = kOffRed + 4096;
constexpr int kOffXn = kOffStamp + 128;
constexpr int kOffPart = kOffXn + kB * kXnStride;
constexpr int kSmemUsed = kOffPart + 4096;
constexpr int kSmemBytes = kSmemUsed + 1024;
static_assert(kSmemBytes <= 232448, "shared memory budget");
static_assert(kSlots * 4 * 8 <= 256, "barrier area");
static_assert(KEARLY <= kWin && KEARLY <= kStatic * 4 && 1 + kStatic == kSlots, "start-up configuration");

constexpr unsigned kSpinLimit = 1u << 26;

struct State {
    unsigned long long ticket;
    unsigned pad0[30];
    unsigned exhausted;
    unsigned pad1[31];
};

__device__ __align__(128) State g_state;
__device__ __align__(128) uint2 g_q[kPairs * 64];
__device__ __align__(128) uint2 g_h[kB * (kF / 2)];
__device__ __align__(128) uint32_t g_score[kPairs * kSK];
__device__ __align__(128) uint32_t g_max[kPairs * 128];
__device__ __align__(128) float g_oacc[kPairs * kDH * 2];
__device__ __align__(128) float g_lacc[kPairs * 32];
__device__ __align__(128) uint2 g_contrib[kSlices * kB * kD];

#define STAMP(i) do { } while (0)

__device__ __forceinline__ uint32_t smem_u32(const void* p) { return (uint32_t)__cvta_generic_to_shared(p); }

__device__ __forceinline__ void mbar_init(uint32_t bar, uint32_t cnt) {
    asm volatile("mbarrier.init.shared::cta.b64 [%0], %1;" ::"r"(bar), "r"(cnt) : "memory");
}
__device__ __forceinline__ void mbar_expect_tx(uint32_t bar, uint32_t bytes) {
    asm volatile("mbarrier.arrive.expect_tx.shared::cta.b64 _, [%0], %1;" ::"r"(bar), "r"(bytes) : "memory");
}
__device__ __forceinline__ void mbar_arrive(uint32_t bar) {
    asm volatile("mbarrier.arrive.shared::cta.b64 _, [%0];" ::"r"(bar) : "memory");
}
__device__ __forceinline__ bool mbar_try(uint32_t bar, uint32_t parity) {
    uint32_t ok;
    asm volatile(
        "{\n.reg .pred p;\n"
        "mbarrier.try_wait.parity.shared::cta.b64 p, [%1], %2;\n"
        "selp.u32 %0, 1, 0, p;\n}"
        : "=r"(ok) : "r"(bar), "r"(parity) : "memory");
    return ok != 0;
}
__device__ __forceinline__ void mbar_wait(uint32_t bar, uint32_t parity) {
    unsigned n = 0;
    while (!mbar_try(bar, parity)) {
        if (++n > kSpinLimit) __trap();
    }
}
__device__ __forceinline__ void bulk_load(uint32_t dst, const void* src, uint32_t bytes, uint32_t bar) {
    asm volatile("cp.async.bulk.shared::cluster.global.mbarrier::complete_tx::bytes [%0], [%1], %2, [%3];"
                 ::"r"(dst), "l"(src), "r"(bytes), "r"(bar) : "memory");
}
__device__ __forceinline__ void bulk_load_hint(uint32_t dst, const void* src, uint32_t bytes, uint32_t bar, uint64_t pol) {
    asm volatile("cp.async.bulk.shared::cluster.global.mbarrier::complete_tx::bytes.L2::cache_hint [%0], [%1], %2, [%3], %4;"
                 ::"r"(dst), "l"(src), "r"(bytes), "r"(bar), "l"(pol) : "memory");
}
__device__ __forceinline__ void tma_load_2d(uint32_t dst, const CUtensorMap* map, int c0, int c1, uint32_t bar) {
    asm volatile("cp.async.bulk.tensor.2d.shared::cluster.global.mbarrier::complete_tx::bytes [%0], [%1, {%3, %4}], [%2];"
                 ::"r"(dst), "l"(map), "r"(bar), "r"(c0), "r"(c1) : "memory");
}
__device__ __forceinline__ void tma_prefetch_2d(const CUtensorMap* map, int c0, int c1) {
    asm volatile("cp.async.bulk.prefetch.tensor.2d.L2.global.tile [%0, {%1, %2}];" ::"l"(map), "r"(c0), "r"(c1) : "memory");
}
__device__ __forceinline__ void cp_async16(uint32_t dst, const void* src) {
    asm volatile("cp.async.cg.shared.global [%0], [%1], 16;" ::"r"(dst), "l"(src) : "memory");
}
__device__ __forceinline__ void cp_async16_pf(uint32_t dst, const void* src) {
    asm volatile("cp.async.cg.shared.global.L2::256B [%0], [%1], 16;" ::"r"(dst), "l"(src) : "memory");
}
__device__ __forceinline__ void cp_async_commit() { asm volatile("cp.async.commit_group;" ::: "memory"); }
template <int N>
__device__ __forceinline__ void cp_async_wait() { asm volatile("cp.async.wait_group %0;" ::"n"(N) : "memory"); }

__device__ __forceinline__ void named_bar(int id, int n) { asm volatile("bar.sync %0, %1;" ::"r"(id), "r"(n) : "memory"); }

__device__ __forceinline__ void ldsm4(uint32_t (&r)[4], uint32_t addr) {
    asm volatile("ldmatrix.sync.aligned.m8n8.x4.shared.b16 {%0,%1,%2,%3}, [%4];"
                 : "=r"(r[0]), "=r"(r[1]), "=r"(r[2]), "=r"(r[3]) : "r"(addr) : "memory");
}
__device__ __forceinline__ void ldsm4t(uint32_t (&r)[4], uint32_t addr) {
    asm volatile("ldmatrix.sync.aligned.m8n8.x4.trans.shared.b16 {%0,%1,%2,%3}, [%4];"
                 : "=r"(r[0]), "=r"(r[1]), "=r"(r[2]), "=r"(r[3]) : "r"(addr) : "memory");
}
__device__ __forceinline__ void mma16816(float (&c)[4], const uint32_t (&a)[4], uint32_t b0, uint32_t b1) {
    asm volatile("mma.sync.aligned.m16n8k16.row.col.f32.bf16.bf16.f32 {%0,%1,%2,%3}, {%4,%5,%6,%7}, {%8,%9}, {%0,%1,%2,%3};"
                 : "+f"(c[0]), "+f"(c[1]), "+f"(c[2]), "+f"(c[3])
                 : "r"(a[0]), "r"(a[1]), "r"(a[2]), "r"(a[3]), "r"(b0), "r"(b1));
}
__device__ __forceinline__ uint32_t lds32(uint32_t a) { uint32_t v; asm volatile("ld.shared.u32 %0, [%1];" : "=r"(v) : "r"(a) : "memory"); return v; }
__device__ __forceinline__ uint2 lds64(uint32_t a) { uint2 v; asm volatile("ld.shared.v2.u32 {%0,%1}, [%2];" : "=r"(v.x), "=r"(v.y) : "r"(a) : "memory"); return v; }
__device__ __forceinline__ uint4 lds128(uint32_t a) { uint4 v; asm volatile("ld.shared.v4.u32 {%0,%1,%2,%3}, [%4];" : "=r"(v.x), "=r"(v.y), "=r"(v.z), "=r"(v.w) : "r"(a) : "memory"); return v; }
__device__ __forceinline__ float lds_f(uint32_t a) { float v; asm volatile("ld.shared.f32 %0, [%1];" : "=f"(v) : "r"(a) : "memory"); return v; }
__device__ __forceinline__ void sts32(uint32_t a, uint32_t v) { asm volatile("st.shared.u32 [%0], %1;" ::"r"(a), "r"(v) : "memory"); }
__device__ __forceinline__ void sts_f(uint32_t a, float v) { asm volatile("st.shared.f32 [%0], %1;" ::"r"(a), "f"(v) : "memory"); }
__device__ __forceinline__ void sts128(uint32_t a, uint4 v) { asm volatile("st.shared.v4.u32 [%0], {%1,%2,%3,%4};" ::"r"(a), "r"(v.x), "r"(v.y), "r"(v.z), "r"(v.w) : "memory"); }

__device__ __forceinline__ uint2 ld_rlx64(const uint2* p) {
    unsigned long long v;
    asm volatile("ld.relaxed.gpu.global.b64 %0, [%1];" : "=l"(v) : "l"(p) : "memory");
    return make_uint2((uint32_t)v, (uint32_t)(v >> 32));
}
__device__ __forceinline__ void st_rlx64(uint2* p, uint32_t lo, uint32_t hi) {
    unsigned long long v = ((unsigned long long)hi << 32) | lo;
    asm volatile("st.relaxed.gpu.global.b64 [%0], %1;" ::"l"(p), "l"(v) : "memory");
}
__device__ __forceinline__ uint4 ld_rlx128(const uint32_t* p) {
    uint4 v;
    asm volatile("ld.relaxed.gpu.global.v4.u32 {%0,%1,%2,%3}, [%4];" : "=r"(v.x), "=r"(v.y), "=r"(v.z), "=r"(v.w) : "l"(p) : "memory");
    return v;
}
__device__ __forceinline__ void st_rlx128(uint32_t* p, uint4 v) {
    asm volatile("st.relaxed.gpu.global.v4.u32 [%0], {%1,%2,%3,%4};" ::"l"(p), "r"(v.x), "r"(v.y), "r"(v.z), "r"(v.w) : "memory");
}
__device__ __forceinline__ void st_rlx32(uint32_t* p, uint32_t v) {
    asm volatile("st.relaxed.gpu.global.u32 [%0], %1;" ::"l"(p), "r"(v) : "memory");
}
__device__ __forceinline__ uint32_t ld_rlx32(const uint32_t* p) {
    uint32_t v;
    asm volatile("ld.relaxed.gpu.global.u32 %0, [%1];" : "=r"(v) : "l"(p) : "memory");
    return v;
}
__device__ __forceinline__ uint32_t ld_acq32(const uint32_t* p) {
    uint32_t v;
    asm volatile("ld.acquire.gpu.global.u32 %0, [%1];" : "=r"(v) : "l"(p) : "memory");
    return v;
}
__device__ __forceinline__ float4 ld_rlx_f4(const float* p) {
    float4 v;
    asm volatile("ld.relaxed.gpu.global.v4.f32 {%0,%1,%2,%3}, [%4];" : "=f"(v.x), "=f"(v.y), "=f"(v.z), "=f"(v.w) : "l"(p) : "memory");
    return v;
}
__device__ __forceinline__ uint32_t ldg_u32(const void* p) { uint32_t v; asm volatile("ld.global.nc.u32 %0, [%1];" : "=r"(v) : "l"(p)); return v; }
__device__ __forceinline__ uint32_t ldg_u16(const void* p) { uint16_t v; asm volatile("ld.global.nc.u16 %0, [%1];" : "=h"(v) : "l"(p)); return v; }
__device__ __forceinline__ void prefetch_l2(const void* p) { asm volatile("prefetch.global.L2 [%0];" ::"l"(p)); }
__device__ __forceinline__ float2 ld_rlx_f2(const float* p) {
    float2 v;
    asm volatile("ld.relaxed.gpu.global.v2.f32 {%0,%1}, [%2];" : "=f"(v.x), "=f"(v.y) : "l"(p) : "memory");
    return v;
}
__device__ __forceinline__ float ld_rlx_f(const float* p) {
    float v;
    asm volatile("ld.relaxed.gpu.global.f32 %0, [%1];" : "=f"(v) : "l"(p) : "memory");
    return v;
}
__device__ __forceinline__ void red_add_2f32(float* p, float a, float b) {
    asm volatile("red.relaxed.gpu.global.add.v2.f32 [%0], {%1, %2};" ::"l"(p), "f"(a), "f"(b) : "memory");
}
__device__ __forceinline__ void red_add_f32(float* p, float v) {
    asm volatile("red.relaxed.gpu.global.add.f32 [%0], %1;" ::"l"(p), "f"(v) : "memory");
}
__device__ __forceinline__ unsigned long long atom_inc_u64(unsigned long long* p) {
    unsigned long long r;
    asm volatile("{\n.reg .u32 l;\n.reg .u64 v;\nmov.u32 l, %%laneid;\nadd.u32 l, l, 1;\ncvt.u64.u32 v, l;\n"
                 "atom.relaxed.gpu.global.add.u64 %0, [%1], v;\n}" : "=l"(r) : "l"(p) : "memory");
    return r;
}
__device__ __forceinline__ unsigned atom_inc_u32(unsigned* p) {
    unsigned r;
    asm volatile("{\n.reg .u32 l;\nmov.u32 l, %%laneid;\nadd.u32 l, l, 1;\n"
                 "atom.relaxed.gpu.global.add.u32 %0, [%1], l;\n}" : "=r"(r) : "l"(p) : "memory");
    return r;
}
__device__ __forceinline__ void red_add_u32(unsigned* p, unsigned v) {
    asm volatile("red.relaxed.gpu.global.add.u32 [%0], %1;" ::"l"(p), "r"(v) : "memory");
}

__device__ __forceinline__ float bfr(float f) { return __bfloat162float(__float2bfloat16_rn(f)); }
__device__ __forceinline__ uint32_t bf_bits(float f) { return (uint32_t)__bfloat16_as_ushort(__float2bfloat16_rn(f)); }
__device__ __forceinline__ uint32_t pack_bf2(float lo, float hi) {
    __nv_bfloat162 v = __floats2bfloat162_rn(lo, hi);
    return *reinterpret_cast<uint32_t*>(&v);
}
__device__ __forceinline__ float bf_lo(uint32_t w) { return __uint_as_float(w << 16); }
__device__ __forceinline__ float bf_hi(uint32_t w) { return __uint_as_float(w & 0xffff0000u); }
__device__ __forceinline__ int ord(uint32_t bits) { int i = (int)bits; return i ^ ((i >> 31) & 0x7fffffff); }
__device__ __forceinline__ float ex2(float x) { float y; asm("ex2.approx.ftz.f32 %0, %1;" : "=f"(y) : "f"(x)); return y; }

__device__ __forceinline__ void decode_unit(uint32_t u, uint32_t& type, uint32_t& pair, uint32_t& tile) {
    const uint32_t blk = u >> 5;
    tile = u & 31;
    if (blk < (uint32_t)kLag) {
        type = kTypeK; pair = blk;
    } else if (blk < (uint32_t)(2 * kPairs - kLag)) {
        const uint32_t g = blk - kLag;
        if (g & 1) { type = kTypeK; pair = kLag + (g >> 1); }
        else       { type = kTypeV; pair = g >> 1; }
    } else {
        type = kTypeV; pair = blk - kPairs;
    }
}

__global__ void __launch_bounds__(kThreads, 1)
fused_decode_kernel(const __nv_bfloat16* __restrict__ x, const __nv_bfloat16* __restrict__ kc,
                    const __nv_bfloat16* __restrict__ vc, const __nv_bfloat16* __restrict__ wq,
                    const __nv_bfloat16* __restrict__ w1, const __nv_bfloat16* __restrict__ b1,
                    const __nv_bfloat16* __restrict__ b2, __nv_bfloat16* __restrict__ out,
                    const __grid_constant__ CUtensorMap map_wo, const __grid_constant__ CUtensorMap map_w2) {
    extern __shared__ uint8_t smem_raw[];
    const uint32_t sbase = (smem_u32(smem_raw) + 1023u) & ~1023u;
    const int tid = threadIdx.x;
    const int warp = tid >> 5;
    const int lane = tid & 31;
    const uint32_t G = gridDim.x;
    const uint32_t cta = blockIdx.x;

    uint64_t pol = 0;
    if (tid == kConsumerThreads) {
        STAMP(0);
        for (uint32_t c = cta; c < 128; c += G)
            asm volatile("cp.async.bulk.prefetch.L2.global [%0], %1;" ::"l"(reinterpret_cast<const char*>(wq) + (size_t)c * 32768), "r"(32768) : "memory");
        for (uint32_t c = cta; c < 112; c += G)
            asm volatile("cp.async.bulk.prefetch.L2.global [%0], %1;" ::"l"(reinterpret_cast<const char*>(w1) + (size_t)c * 16384), "r"(16384) : "memory");
        asm volatile("createpolicy.fractional.L2::evict_first.b64 %0, 1.0;" : "=l"(pol));
#pragma unroll 1
        for (int i = 0; i < kSlots * 4; i++) mbar_init(sbase + kOffFull + i * 8, 1);
        asm volatile("fence.mbarrier_init.release.cluster;" ::: "memory");
#pragma unroll 1
        for (int i = 0; i < KFAST; i++) {
            const uint32_t full = sbase + kOffFull + (4 + i) * 8;
            mbar_expect_tx(full, kPieceBytes);
            bulk_load_hint(sbase + (1 + (i >> 2)) * kSlotBytes + (i & 3) * kPieceBytes,
                           kc + ((size_t)(cta + (i >> 2) * G) * kTileKeys + (i & 3) * 32) * kDH, kPieceBytes, full, pol);
        }
    }

    if (warp == 4) {
        uint32_t slot = 1, phase = 0;
        int tc = 4 - kWin;
        uint32_t tb = (uint32_t)((4 - kWin + 4 * kSlots) % (4 * kSlots)), tphase = 0;
        auto window = [&](bool wait = true) {
            if (wait && tc >= 4) mbar_wait(sbase + kOffFull + tb * 8, tphase);
            ++tc;
            if (++tb == 4u * kSlots) { tb = 0; if (tc > 0) tphase ^= 1; }
        };
        auto wait_empty = [&]() { mbar_wait(sbase + kOffEmpty + slot * 8, phase ^ 1); };
        auto advance = [&]() { if (++slot == (uint32_t)kSlots) { slot = 0; phase ^= 1; } };
        auto issue_piece = [&](uint32_t type, uint32_t pair, uint32_t tile, int p) {
            window();
            {
                const uint32_t full = sbase + kOffFull + (slot * 4 + p) * 8;
                const uint32_t dst = sbase + slot * kSlotBytes;
                const size_t off = ((size_t)pair * kSK + (size_t)tile * kTileKeys + p * 32) * kDH;
                const __nv_bfloat16* src = (type == kTypeK ? kc : vc) + off;
                if (p == 0) {
                    sts32(sbase + kOffDesc + slot * 4, type | (pair << 3) | (tile << 11));
                    if (type == kTypeK) {
                        mbar_expect_tx(full, kPieceBytes + 512);
                        bulk_load(dst + kTileBytes, g_q + pair * 64, 512, full);
                    } else {
                        mbar_expect_tx(full, kPieceBytes + 1024);
                        bulk_load(dst + kTileBytes, g_score + pair * kSK + tile * kTileKeys, 512, full);
                        bulk_load(dst + kTileBytes + 512, g_max + pair * 128, 512, full);
                    }
                } else {
                    mbar_expect_tx(full, kPieceBytes);
                }
                bulk_load_hint(dst + p * kPieceBytes, src, kPieceBytes, full, pol);
            }
        };
        unsigned long long ticket = 0;
        if (lane == 0) {
            for (int i = 0; i < kSlots; i++) mbar_init(sbase + kOffEmpty + i * 8, 4);
            mbar_init(sbase + kOffEpochBar, 1);
            asm volatile("fence.mbarrier_init.release.cluster;" ::: "memory");
            for (int i = 0; i < 4; i++) mbar_arrive(sbase + kOffFull + i * 8);
            for (int k = 0; k < kStatic; k++) {
                const uint32_t u = cta + k * G;
                sts32(sbase + kOffDesc + (1 + k) * 4, kTypeK | ((u >> 5) << 3) | ((u & 31) << 11) | kDescNoAux);
            }
            ticket = atom_inc_u64(&g_state.ticket);
        }
        named_bar(2, kThreads);
        if (lane == 0) {
#pragma unroll 1
            for (int i = KFAST; i < KEARLY; i++) {
                const uint32_t full = sbase + kOffFull + (4 + i) * 8;
                mbar_expect_tx(full, kPieceBytes);
                bulk_load_hint(sbase + (1 + (i >> 2)) * kSlotBytes + (i & 3) * kPieceBytes,
                               kc + ((size_t)(cta + (i >> 2) * G) * kTileKeys + (i & 3) * 32) * kDH, kPieceBytes, full, pol);
            }
            asm volatile("" ::: "memory");
            sts32(sbase + kOffEpoch, (uint32_t)(ticket >> 32));
            mbar_arrive(sbase + kOffEpochBar);
            asm volatile("prefetch.tensormap [%0];" ::"l"(&map_wo) : "memory");
            asm volatile("prefetch.tensormap [%0];" ::"l"(&map_w2) : "memory");
        }
        __syncwarp();
#pragma unroll 1
        for (int i = 0; i < kStatic * 4; i++) {
            if (i >= KEARLY) {
                window(true);
                if (lane == 0) {
                    const uint32_t full = sbase + kOffFull + (4 + i) * 8;
                    mbar_expect_tx(full, kPieceBytes);
                    bulk_load_hint(sbase + (1 + (i >> 2)) * kSlotBytes + (i & 3) * kPieceBytes,
                                   kc + ((size_t)(cta + (i >> 2) * G) * kTileKeys + (i & 3) * 32) * kDH, kPieceBytes, full, pol);
                }
            } else {
                window(false);
            }
        }
        slot = (1 + kStatic) % kSlots;
        phase = (1 + kStatic) / kSlots;
        for (uint32_t ft = cta; ft < (uint32_t)kFTasks; ft += G) {
            wait_empty();
#pragma unroll 1
            for (int p = 0; p < 4; p++) {
                window();
                const uint32_t full = sbase + kOffFull + (slot * 4 + p) * 8;
                const __nv_bfloat16* src = w1 + ft * 16 + (size_t)(p * 128 + (lane >> 1)) * kF + (lane & 1) * 8;
                const uint32_t dst = sbase + slot * kSlotBytes + (p * 128 + (lane >> 1)) * 32 + (((lane & 1) ^ ((lane >> 3) & 1)) << 4);
#pragma unroll
                for (int i = 0; i < 8; i++) cp_async16_pf(dst + i * 512, src + (size_t)i * 16 * kF);
                asm volatile("cp.async.mbarrier.arrive.shared::cta.b64 [%0];" ::"r"(full) : "memory");
                __syncwarp();
                if (lane == 0) {
                    if (p == 0) sts32(sbase + kOffDesc + slot * 4, kTypeF | (ft << 3));
                    mbar_arrive(full);
                }
            }
            advance();
        }
        auto issue_proj = [&](uint32_t slice, uint32_t quarter, bool use_window) {
            const uint32_t dst = sbase + slot * kSlotBytes;
            wait_empty();
            const CUtensorMap* map = (slice < (uint32_t)kH) ? &map_wo : &map_w2;
            const int row = (int)((slice < (uint32_t)kH) ? slice : slice - kH) * 128;
            sts32(sbase + kOffDesc + slot * 4, kTypeP | (slice << 3) | (quarter << 11));
            for (int p = 0; p < 4; p++) {
                const uint32_t full = sbase + kOffFull + (slot * 4 + p) * 8;
                if (use_window) window();
                mbar_expect_tx(full, kPieceBytes);
                tma_load_2d(dst + p * kPieceBytes, map, (int)quarter * 128 + p * 32, row, full);
            }
            advance();
        };
        if (lane == 0) {
            uint32_t pending = (uint32_t)ticket;
            uint32_t u = pending + kStatic * G;
            while (u < (uint32_t)kTickets) {
                if (u >= (uint32_t)kFfnPos && u < (uint32_t)(kFfnPos + kFfnUnits)) {
                    pending = (uint32_t)atom_inc_u64(&g_state.ticket);
                    const uint32_t f = u - kFfnPos;
                    issue_proj(kH + (f >> 2), f & 3, true);
                } else {
                    uint32_t type, pair, tile;
                    decode_unit(u < (uint32_t)kFfnPos ? u : u - kFfnUnits, type, pair, tile);
                    wait_empty();
                    issue_piece(type, pair, tile, 0);
                    pending = (uint32_t)atom_inc_u64(&g_state.ticket);
#pragma unroll 1
                    for (int p = 1; p < 4; p++) issue_piece(type, pair, tile, p);
                    advance();
                }
                u = pending + kStatic * G;
            }
        }
        __syncwarp();
        if (cta < (uint32_t)kAttnUnits) {
            prefetch_l2(g_oacc + ((lane >> 2) * kH + (cta >> 2)) * (kDH * 2) + (lane & 3) * 64);
            prefetch_l2(g_oacc + ((lane >> 2) * kH + (cta >> 2)) * (kDH * 2) + (lane & 3) * 64 + 32);
            if (lane < 8) prefetch_l2(g_lacc + (lane * kH + (cta >> 2)) * 32);
            if (lane < 2 * kFSlices) prefetch_l2(g_contrib + (size_t)(kH + (lane >> 1)) * (kB * kD) + cta * 32 + (lane & 1) * 16);
        }
        for (uint32_t un = cta; un < (uint32_t)kAttnUnits; un += G) {
            uint2* cp = g_contrib + (size_t)(un >> 2) * (kB * kD) + (un & 3) * 128 + (lane >> 2) * kD + (lane & 3) * 2;
#pragma unroll 4
            for (int i = 0; i < 16; i++) st_rlx128(reinterpret_cast<uint32_t*>(cp + i * 8), make_uint4(0u, 0u, 0u, 0u));
        }
        __syncwarp();
        if (lane != 0) return;
        const uint32_t lslot = (slot == 0) ? kSlots - 1 : slot - 1;
        const uint32_t lphase = (slot == 0) ? phase ^ 1 : phase;
        wait_empty();
        sts32(sbase + kOffDesc + slot * 4, kTypeSignal);
        for (int p = 0; p < 4; p++) mbar_arrive(sbase + kOffFull + (slot * 4 + p) * 8);
        advance();
        for (int p = 0; p < 4; p++) mbar_wait(sbase + kOffFull + (lslot * 4 + p) * 8, lphase);
        for (uint32_t a = cta; a < (uint32_t)kAttnUnits; a += G) issue_proj(a >> 2, a & 3, false);
        if (atom_inc_u32(&g_state.exhausted) == G - 1) {
            g_state.exhausted = 0;
            g_state.ticket = ((ticket >> 32) + 1) << 32;
        }
        return;
    }

    const int g = lane >> 2;
    const int j = lane & 3;
    const int mi = lane >> 3;
    const int r = lane & 7;
    const bool diag = (j == (g >> 1));

    const uint32_t s_wq = sbase;
    const uint32_t s_xn = sbase + kOffXn;
    const uint32_t s_part = sbase + kOffPart;

    auto load_wq = [&](uint32_t task) {
        const __nv_bfloat16* src = wq + task * 32 + (size_t)(tid >> 2) * (kH * kDH) + (tid & 3) * 8;
        const uint32_t dst = s_wq + (tid >> 2) * 64 + (((tid & 3) ^ ((tid >> 3) & 3)) << 4);
#pragma unroll 4
        for (int i = 0; i < 16; i++) cp_async16_pf(dst + i * 2048, src + (size_t)i * 32 * (kH * kDH));
    };
#pragma unroll
    for (int i = 0; i < 4; i++) {
        const int row = warp * 2 + (i >> 1), ch = lane + (i & 1) * 32;
        cp_async16(s_xn + row * kXnStride + ch * 16, x + row * kD + ch * 8);
    }
    cp_async_commit();
    for (uint32_t qt = cta; qt < (uint32_t)kQTasks; qt += G)
        st_rlx64(g_q + ((tid >> 4) * kH + (qt >> 2)) * 64 + (qt & 3) * 16 + (tid & 15), 0u, 0u);
    uint32_t b1raw = 0, fxraw = 0, fb2raw = 0;
    if (tid < 64 && cta < (uint32_t)kFTasks) b1raw = ldg_u32(b1 + cta * 16 + 2 * (tid & 7));
    if (cta < (uint32_t)kFinalTasks) {
        fxraw = ldg_u16(x + cta * 32 + warp * 8 + (lane & 7));
        fb2raw = ldg_u16(b2 + ((cta * 32 + warp * 8 + (lane & 7)) & (kD - 1)));
    }
    named_bar(2, kThreads);

    cp_async_wait<0>();
    if (cta < (uint32_t)kQTasks) load_wq(cta);
    cp_async_commit();
    __syncwarp();
    if (tid == 0) STAMP(10);
    {
        float v[2][16];
        float s[2], q2[2];
#pragma unroll
        for (int rr = 0; rr < 2; rr++) {
            const uint32_t a = s_xn + (warp * 2 + rr) * kXnStride + lane * 32;
            const uint4 x0 = lds128(a), x1 = lds128(a + 16);
            const uint32_t w[8] = {x0.x, x0.y, x0.z, x0.w, x1.x, x1.y, x1.z, x1.w};
#pragma unroll
            for (int i = 0; i < 8; i++) { v[rr][2 * i] = bf_lo(w[i]); v[rr][2 * i + 1] = bf_hi(w[i]); }
            float s0 = 0.f, s1 = 0.f, s2 = 0.f, s3 = 0.f;
#pragma unroll
            for (int i = 0; i < 4; i++) { s0 += v[rr][i]; s1 += v[rr][4 + i]; s2 += v[rr][8 + i]; s3 += v[rr][12 + i]; }
            s[rr] = (s0 + s1) + (s2 + s3);
        }
#pragma unroll
        for (int o = 16; o > 0; o >>= 1) {
            s[0] += __shfl_xor_sync(0xffffffffu, s[0], o);
            s[1] += __shfl_xor_sync(0xffffffffu, s[1], o);
        }
#pragma unroll
        for (int rr = 0; rr < 2; rr++) {
            const float mean = s[rr] * (1.0f / kD);
            s[rr] = mean;
            float t0 = 0.f, t1 = 0.f, t2 = 0.f, t3 = 0.f;
#pragma unroll
            for (int i = 0; i < 4; i++) {
                const float d0 = v[rr][i] - mean, d1 = v[rr][4 + i] - mean, d2 = v[rr][8 + i] - mean, d3 = v[rr][12 + i] - mean;
                t0 += d0 * d0; t1 += d1 * d1; t2 += d2 * d2; t3 += d3 * d3;
            }
            q2[rr] = (t0 + t1) + (t2 + t3);
        }
#pragma unroll
        for (int o = 16; o > 0; o >>= 1) {
            q2[0] += __shfl_xor_sync(0xffffffffu, q2[0], o);
            q2[1] += __shfl_xor_sync(0xffffffffu, q2[1], o);
        }
#pragma unroll
        for (int rr = 0; rr < 2; rr++) {
            const float mb = bfr(s[rr]);
            const float vb = bfr(q2[rr] * (1.0f / kD));
            const float sd = bfr(__fsqrt_rn(bfr(vb + 1e-5f)));
            const float rs = __frcp_rn(sd);
            uint32_t o[8];
#pragma unroll
            for (int i = 0; i < 8; i++) o[i] = pack_bf2(bfr(v[rr][2 * i] - mb) * rs, bfr(v[rr][2 * i + 1] - mb) * rs);
            const uint32_t a = s_xn + (warp * 2 + rr) * kXnStride + lane * 32;
            sts128(a, make_uint4(o[0], o[1], o[2], o[3]));
            sts128(a + 16, make_uint4(o[4], o[5], o[6], o[7]));
        }
    }

    uint32_t epoch = 0, tag32 = 0;
#pragma unroll 1
    for (uint32_t qt = cta; qt < (uint32_t)kQTasks; qt += G) {
        if (qt != cta) {
            named_bar(1, kConsumerThreads);
            load_wq(qt);
            cp_async_commit();
        }
        cp_async_wait<0>();
        named_bar(1, kConsumerThreads);
        float acc[2][2][4] = {};
        const uint32_t a0 = s_wq + (warp * 128 + (mi >> 1) * 8 + r) * 64 + (((mi & 1) ^ ((r >> 1) & 3)) << 4);
        const uint32_t b0 = s_xn + g * kXnStride + (warp * 128 + 2 * j) * 2;
#pragma unroll
        for (int ks = 0; ks < 8; ks++) {
            const uint32_t bx0 = lds32(b0 + ks * 32), bx1 = lds32(b0 + ks * 32 + 16);
#pragma unroll
            for (int mt = 0; mt < 2; mt++) {
                uint32_t a[4];
                ldsm4t(a, (a0 + ks * 1024) ^ (mt << 5));
                mma16816(acc[mt][ks & 1], a, bx0, bx1);
            }
        }
#pragma unroll
        for (int mt = 0; mt < 2; mt++) {
            const uint32_t p = s_part + (warp * 32 + mt * 16 + g) * 32 + j * 8;
            sts_f(p, acc[mt][0][0] + acc[mt][1][0]); sts_f(p + 4, acc[mt][0][1] + acc[mt][1][1]);
            sts_f(p + 256, acc[mt][0][2] + acc[mt][1][2]); sts_f(p + 260, acc[mt][0][3] + acc[mt][1][3]);
        }
        named_bar(1, kConsumerThreads);
        mbar_wait(sbase + kOffEpochBar, 0);
        tag32 = lds32(sbase + kOffEpoch) + 1;
        const int b = tid >> 4, cp = tid & 15;
        float v0 = 0.f, v1 = 0.f;
#pragma unroll
        for (int w = 0; w < 4; w++) {
            v0 += lds_f(s_part + (w * 32 + 2 * cp) * 32 + b * 4);
            v1 += lds_f(s_part + (w * 32 + 2 * cp + 1) * 32 + b * 4);
        }
        st_rlx64(g_q + (b * kH + (qt >> 2)) * 64 + (qt & 3) * 16 + cp, pack_bf2(v0, v1), tag32);
    }
    if (tid == 0) STAMP(1);
    cp_async_wait<0>();
    asm volatile("fence.proxy.async.shared::cta;" ::: "memory");
    named_bar(1, kConsumerThreads);
    if (lane == 0) mbar_arrive(sbase + kOffEmpty + 0);
    mbar_wait(sbase + kOffEpochBar, 0);
    epoch = lds32(sbase + kOffEpoch);
    tag32 = epoch + 1;
    const uint32_t tag16 = (epoch % 65535u) + 1u;

    const uint32_t k_lane_off = (uint32_t)(warp * 32 + (mi & 1) * 8 + r) * 256u + (uint32_t)(((r & 6) | ((mi >> 1) ^ (r & 1))) << 4);
    const uint32_t v_lane_off = (uint32_t)(warp * 32 + (mi >> 1) * 8 + r) * 256u + (uint32_t)(((r & 6) | ((mi & 1) ^ (r & 1))) << 4);
    constexpr float kScale = 0.08838834764831845f;
    constexpr float kLog2e = 1.4426950408889634f;

    uint32_t slot = 1, phase = 0, rbuf = 0;
    float* const oacc = g_oacc;
    float* const lacc = g_lacc;
    const float cnt_base = (float)((epoch & 1023u) * 64u);
    const float cnt_full = cnt_base + (float)kTilesPerPair;
    auto stage_input = [&](uint32_t slice) {
        const int sb = tid >> 4, sc = tid & 15;
        uint4 inw;
        if (slice >= (uint32_t)kH) {
            const uint2* hp = g_h + sb * (kF / 2) + (slice - kH) * 64 + sc * 4;
            unsigned it = 0;
            bool ok;
            do {
                const uint2 w0 = ld_rlx64(hp), w1_ = ld_rlx64(hp + 1), w2_ = ld_rlx64(hp + 2), w3 = ld_rlx64(hp + 3);
                ok = (w0.y == tag32) && (w1_.y == tag32) && (w2_.y == tag32) && (w3.y == tag32);
                inw = make_uint4(w0.x, w1_.x, w2_.x, w3.x);
                if (++it > kSpinLimit) __trap();
            } while (!__all_sync(0xffffffffu, ok));
        } else {
            const float* op = g_oacc + ((sb * kH + slice) * kDH + sc * 2) * 2;
            const float* lp = g_lacc + (sb * kH + slice) * 32;
            float4 v[4];
            float2 lv;
            unsigned it = 0;
            if (tid == 0) STAMP(13);
            while (true) {
                float4 c[4];
#pragma unroll
                for (int i = 0; i < 4; i++) c[i] = ld_rlx_f4(op + i * 64);
                const float2 lc = ld_rlx_f2(lp);
#pragma unroll
                for (int i = 0; i < 4; i++) v[i] = ld_rlx_f4(op + i * 64);
                lv = ld_rlx_f2(lp);
                bool ok = (lc.y == cnt_full);
#pragma unroll
                for (int i = 0; i < 4; i++) ok = ok && (c[i].y == cnt_full) && (c[i].w == cnt_full);
                if (ok) break;
                if (++it > kSpinLimit) __trap();
            }
            if (tid == 0) STAMP(4);
            const float inv = __frcp_rn(lv.x);
            named_bar(1, kConsumerThreads);
#pragma unroll
            for (int i = 0; i < 4; i++) sts32(s_part + sb * kInStride + (i * 32 + sc * 2) * 2, pack_bf2(v[i].x * inv, v[i].z * inv));
            named_bar(1, kConsumerThreads);
            return;
        }
        named_bar(1, kConsumerThreads);
        sts128(s_part + sb * kInStride + sc * 16, inw);
        named_bar(1, kConsumerThreads);
    };
    uint32_t attn_left = 0, attn_next = 0;
    bool staged = false;
    auto wait_unit = [&]() {
        mbar_wait(sbase + kOffFull + slot * 32, phase);
        if (warp != 0) mbar_wait(sbase + kOffFull + slot * 32 + warp * 8, phase);
    };

#pragma unroll 1
    while (true) {
        const uint32_t tile_base = sbase + slot * kSlotBytes;
        const uint32_t aux = tile_base + kTileBytes;
        const uint32_t empty_bar = sbase + kOffEmpty + slot * 8;
        wait_unit();
        const uint32_t desc = lds32(sbase + kOffDesc + slot * 4);
        if (++slot == (uint32_t)kSlots) { slot = 0; phase ^= 1; }
        const uint32_t type = desc & 7;

        if (type == kTypeK) {
            const uint32_t pair = (desc >> 3) & 255, tile = (desc >> 11) & 31;
            uint32_t qf[16];
            bool ok = !(desc & kDescNoAux);
#pragma unroll
            for (int t = 0; t < 8; t++) {
                const uint2 a = lds64(aux + ((((2 * t) ^ g) * 4 + j) << 3));
                const uint2 b = lds64(aux + ((((2 * t + 1) ^ g) * 4 + j) << 3));
                ok = ok && (a.y == tag32) && (b.y == tag32);
                qf[2 * t] = a.x; qf[2 * t + 1] = b.x;
            }
            if (!__all_sync(0xffffffffu, ok)) {
                named_bar(1, kConsumerThreads);
                if (tid < 64) {
                    unsigned n = 0;
                    const uint2* qp = g_q + pair * 64 + tid;
                    uint2 w = ld_rlx64(qp);
                    while (w.y != tag32) {
                        w = ld_rlx64(qp);
                        if (++n > kSpinLimit) __trap();
                    }
                    sts32(aux + tid * 8, w.x);
                    asm volatile("fence.proxy.async.shared::cta;" ::: "memory");
                }
                named_bar(1, kConsumerThreads);
#pragma unroll
                for (int t = 0; t < 8; t++) {
                    qf[2 * t] = lds32(aux + ((((2 * t) ^ g) * 4 + j) << 3));
                    qf[2 * t + 1] = lds32(aux + ((((2 * t + 1) ^ g) * 4 + j) << 3));
                }
            }
            float acc[2][2][4] = {};
#pragma unroll
            for (int mt = 0; mt < 2; mt++) {
                const uint32_t a0 = tile_base + k_lane_off + mt * 4096;
#pragma unroll
                for (int t = 0; t < 8; t++) {
                    uint32_t a[4];
                    ldsm4(a, a0 ^ (t << 5));
                    mma16816(acc[mt][t & 1], a, qf[2 * t], qf[2 * t + 1]);
                }
            }
            uint32_t wv[4];
            int mo = INT_MIN;
#pragma unroll
            for (int i = 0; i < 4; i++) {
                const int mt = i >> 1, hf = i & 1;
                const float c0 = acc[mt][0][hf * 2] + acc[mt][1][hf * 2];
                const float c1 = acc[mt][0][hf * 2 + 1] + acc[mt][1][hf * 2 + 1];
                const float c = (g & 1) ? c1 : c0;
                const uint32_t bits = __float_as_uint(bfr(bfr(c) * kScale));
                wv[i] = bits | tag16;
                mo = max(mo, ord(bits));
            }
            __syncwarp();
            if (lane == 0) mbar_arrive(empty_bar);
            mo = __reduce_max_sync(0xffffffffu, diag ? mo : INT_MIN);
            if (diag) st_rlx128(g_score + pair * kSK + tile * kTileKeys + warp * 32 + g * 4, make_uint4(wv[0], wv[1], wv[2], wv[3]));
            if (tile == 0 && warp == 0) {
                const uint32_t cb = __float_as_uint(cnt_base);
                st_rlx128(reinterpret_cast<uint32_t*>(oacc + pair * (kDH * 2)) + lane * 4, make_uint4(0u, cb, 0u, cb));
                st_rlx128(reinterpret_cast<uint32_t*>(oacc + pair * (kDH * 2)) + 128 + lane * 4, make_uint4(0u, cb, 0u, cb));
                st_rlx32(reinterpret_cast<uint32_t*>(lacc + pair * 32) + lane, lane == 1 ? cb : 0u);
                asm volatile("fence.acq_rel.gpu;" ::: "memory");
            }
            if (lane == 0) st_rlx32(g_max + pair * 128 + tile * 4 + warp, ((uint32_t)ord((uint32_t)mo) & 0xffff0000u) | tag16);
        } else if (type == kTypeV) {
            const uint32_t pair = (desc >> 3) & 255, tile = (desc >> 11) & 31;
            uint4 sw = lds128(aux + (warp * 32 + g * 4) * 4);
            uint4 mw = lds128(aux + 512 + lane * 16);
            auto tags_ok = [&](const uint4& a) {
                return ((a.x & 0xffffu) == tag16) && ((a.y & 0xffffu) == tag16) && ((a.z & 0xffffu) == tag16) && ((a.w & 0xffffu) == tag16);
            };
            if (!__all_sync(0xffffffffu, tags_ok(sw) && tags_ok(mw))) {
                unsigned n = 0;
                do {
                    sw = ld_rlx128(g_score + pair * kSK + tile * kTileKeys + warp * 32 + g * 4);
                    mw = ld_rlx128(g_max + pair * 128 + lane * 4);
                    if (++n > kSpinLimit) __trap();
                } while (!__all_sync(0xffffffffu, tags_ok(sw) && tags_ok(mw)));
            }
            int mo = max(max(ord(mw.x & 0xffff0000u), ord(mw.y & 0xffff0000u)), max(ord(mw.z & 0xffff0000u), ord(mw.w & 0xffff0000u)));
            mo = __reduce_max_sync(0xffffffffu, mo);
            const float M = __uint_as_float((uint32_t)ord((uint32_t)mo));
            const uint32_t swv[4] = {sw.x, sw.y, sw.z, sw.w};
            uint32_t pb[4];
            float lsum = 0.f;
#pragma unroll
            for (int i = 0; i < 4; i++) {
                const float p = ex2((bf_hi(swv[i]) - M) * kLog2e);
                lsum += p;
                const uint32_t bits = bf_bits(p);
                pb[i] = diag ? ((g & 1) ? (bits << 16) : bits) : 0u;
            }
            lsum = diag ? lsum : 0.f;
            float acc[8][4] = {};
#pragma unroll
            for (int ks = 0; ks < 2; ks++) {
                const uint32_t a0 = tile_base + v_lane_off + ks * 4096;
#pragma unroll
                for (int t = 0; t < 8; t++) {
                    uint32_t a[4];
                    ldsm4t(a, a0 ^ (t << 5));
                    mma16816(acc[t], a, pb[2 * ks], pb[2 * ks + 1]);
                }
            }
            __syncwarp();
            if (lane == 0) mbar_arrive(empty_bar);
#pragma unroll
            for (int o = 16; o > 0; o >>= 1) lsum += __shfl_xor_sync(0xffffffffu, lsum, o);
            float U[16];
#pragma unroll
            for (int t = 0; t < 8; t++) { U[2 * t] = acc[t][0] + acc[t][3]; U[2 * t + 1] = acc[t][2] + acc[t][1]; }
            float W[8];
#pragma unroll
            for (int q = 0; q < 8; q++) {
                const int rr = (q & 1) | ((q >> 1) << 2);
                W[q] = U[rr] + __shfl_xor_sync(0xffffffffu, U[rr ^ 2], 1);
            }
            const uint32_t redb = sbase + kOffRed + rbuf * 2048 + warp * 512;
#pragma unroll
            for (int q = 0; q < 4; q++) {
                const int rr = (q & 1) | ((q >> 1) << 3);
                const int iw = (rr & 1) | ((rr >> 2) << 1);
                const int iw4 = ((rr ^ 4) & 1) | (((rr ^ 4) >> 2) << 1);
                const float X = W[iw] + __shfl_xor_sync(0xffffffffu, W[iw4], 2);
                sts_f(redb + (((rr ^ (2 * j)) * 8 + g) << 2), X);
            }
            if (lane == 0) sts_f(sbase + kOffL + rbuf * 16 + warp * 4, lsum);
            named_bar(1, kConsumerThreads);
            {
                const uint32_t rb = sbase + kOffRed + rbuf * 2048 + tid * 4;
                const float s = (lds_f(rb) + lds_f(rb + 512)) + (lds_f(rb + 1024) + lds_f(rb + 1536));
                red_add_2f32(oacc + (pair * kDH + tid) * 2, s, 1.0f);
                if (tid == 0) {
                    const uint32_t lb = sbase + kOffL + rbuf * 16;
                    red_add_2f32(lacc + pair * 32, (lds_f(lb) + lds_f(lb + 4)) + (lds_f(lb + 8) + lds_f(lb + 12)), 1.0f);
                }
            }
            rbuf ^= 1;
        } else if (type == kTypeF) {
            const uint32_t ft = desc >> 3;
            float acc[4] = {};
            const uint32_t a0 = tile_base + (warp * 128 + (mi >> 1) * 8 + r) * 32 + (((mi & 1) ^ ((r >> 2) & 1)) << 4);
            const uint32_t b0 = s_xn + g * kXnStride + (warp * 128 + 2 * j) * 2;
#pragma unroll
            for (int ks = 0; ks < 8; ks++) {
                uint32_t a[4];
                ldsm4t(a, a0 + ks * 512);
                mma16816(acc, a, lds32(b0 + ks * 32), lds32(b0 + ks * 32 + 16));
            }
            __syncwarp();
            if (lane == 0) mbar_arrive(empty_bar);
            named_bar(1, kConsumerThreads);
            const uint32_t p = s_part + (warp * 16 + g) * 32 + j * 8;
            sts_f(p, acc[0]); sts_f(p + 4, acc[1]);
            sts_f(p + 256, acc[2]); sts_f(p + 260, acc[3]);
            named_bar(1, kConsumerThreads);
            if (tid < 64) {
                const int b = tid >> 3, cp = tid & 7;
                const uint32_t bw = (ft == cta) ? b1raw : ldg_u32(b1 + ft * 16 + 2 * cp);
                float v[2];
#pragma unroll
                for (int e = 0; e < 2; e++) {
                    float s = 0.f;
#pragma unroll
                    for (int w = 0; w < 4; w++) s += lds_f(s_part + (w * 16 + 2 * cp + e) * 32 + b * 4);
                    const float hh = bfr(bfr(s) + (e ? bf_hi(bw) : bf_lo(bw)));
                    const float inner = 0.7978845608028654f * (hh + 0.044715f * hh * hh * hh);
                    v[e] = 0.5f * hh * (1.0f + tanhf(inner));
                }
                st_rlx64(g_h + b * (kF / 2) + ft * 8 + cp, pack_bf2(v[0], v[1]), tag32);
            }
        } else if (type == kTypeP) {
            const uint32_t slice = (desc >> 3) & 255, quarter = (desc >> 11) & 3;
            if (tid == 0 && staged) STAMP(8);
            if (!staged) stage_input(slice);
            staged = false;
            uint32_t bf[8][2];
#pragma unroll
            for (int ks = 0; ks < 8; ks++) {
                const uint32_t a = s_part + g * kInStride + (ks * 16 + 2 * j) * 2;
                bf[ks][0] = lds32(a);
                bf[ks][1] = lds32(a + 16);
            }
            float acc[2][2][4] = {};
            const uint32_t a0 = tile_base + warp * kPieceBytes + ((mi >> 1) * 8 + r) * 64 + (((mi & 1) ^ ((r >> 1) & 3)) << 4);
#pragma unroll
            for (int ks = 0; ks < 8; ks++) {
#pragma unroll
                for (int mt = 0; mt < 2; mt++) {
                    uint32_t a[4];
                    ldsm4t(a, (a0 + ks * 1024) ^ (mt << 5));
                    mma16816(acc[mt][ks & 1], a, bf[ks][0], bf[ks][1]);
                }
            }
            uint2* cp = g_contrib + (size_t)slice * (kB * kD) + quarter * 128 + warp * 32 + g;
#pragma unroll
            for (int mt = 0; mt < 2; mt++) {
                st_rlx64(cp + (2 * j) * kD + mt * 16, __float_as_uint(acc[mt][0][0] + acc[mt][1][0]), tag32);
                st_rlx64(cp + (2 * j + 1) * kD + mt * 16, __float_as_uint(acc[mt][0][1] + acc[mt][1][1]), tag32);
                st_rlx64(cp + (2 * j) * kD + mt * 16 + 8, __float_as_uint(acc[mt][0][2] + acc[mt][1][2]), tag32);
                st_rlx64(cp + (2 * j + 1) * kD + mt * 16 + 8, __float_as_uint(acc[mt][0][3] + acc[mt][1][3]), tag32);
            }
            __syncwarp();
            if (lane == 0) mbar_arrive(empty_bar);
            if (attn_left > 0) {
                if (--attn_left == 0) break;
                attn_next += G;
                stage_input(attn_next >> 2);
                staged = true;
            }
        } else {
            __syncwarp();
            if (lane == 0) mbar_arrive(empty_bar);
            if (tid == 0) STAMP(3);
            for (uint32_t a = cta; a < (uint32_t)kAttnUnits; a += G) attn_left++;
            if (attn_left == 0) break;
            attn_next = cta;
            stage_input(cta >> 2);
            staged = true;
            if (tid == 0) STAMP(9);

        }
    }
    if (tid == 0) STAMP(5);

#pragma unroll 1
    for (uint32_t task = cta; task < (uint32_t)kFinalTasks; task += G) {
        const int hg = lane >> 3;
        const uint32_t o = task * 32 + warp * 8 + (lane & 7);
        if (task != cta) {
            fxraw = ldg_u16(x + o);
            fb2raw = ldg_u16(b2 + (o & (kD - 1)));
        }
        const uint2* cp = g_contrib + o;
        uint2 va[8], vb[4];
#pragma unroll
        for (int i = 0; i < 8; i++) va[i] = ld_rlx64(cp + (size_t)(hg * 8 + i) * (kB * kD));
#pragma unroll
        for (int i = 0; i < 4; i++) {
            const int f = hg * 4 + i;
            vb[i] = (f < kFSlices) ? ld_rlx64(cp + (size_t)(kH + f) * (kB * kD)) : make_uint2(0u, tag32);
        }
        unsigned it = 0;
        while (true) {
            bool ok = true;
#pragma unroll
            for (int i = 0; i < 8; i++) ok = ok && (va[i].y == tag32);
#pragma unroll
            for (int i = 0; i < 4; i++) ok = ok && (vb[i].y == tag32);
            if (__all_sync(0xffffffffu, ok)) break;
            if (FINAL_SLEEP > 0) __nanosleep(FINAL_SLEEP);
#pragma unroll
            for (int i = 0; i < 8; i++)
                if (va[i].y != tag32) va[i] = ld_rlx64(cp + (size_t)(hg * 8 + i) * (kB * kD));
#pragma unroll
            for (int i = 0; i < 4; i++)
                if (vb[i].y != tag32) vb[i] = ld_rlx64(cp + (size_t)(kH + hg * 4 + i) * (kB * kD));
            if (++it > kSpinLimit) __trap();
        }
        float sa = 0.f, sb = 0.f;
#pragma unroll
        for (int i = 0; i < 8; i++) sa += __uint_as_float(va[i].x);
#pragma unroll
        for (int i = 0; i < 4; i++) sb += __uint_as_float(vb[i].x);
        sa += __shfl_xor_sync(0xffffffffu, sa, 8);
        sb += __shfl_xor_sync(0xffffffffu, sb, 8);
        sa += __shfl_xor_sync(0xffffffffu, sa, 16);
        sb += __shfl_xor_sync(0xffffffffu, sb, 16);
        if (hg == 0) {
            const float res = bfr(bf_lo(fxraw) + bfr(sa)) + bfr(bfr(sb) + bf_lo(fb2raw));
            out[o] = __float2bfloat16_rn(res);
        }
    }
}

}

typedef CUresult (*EncodeTiledFn)(CUtensorMap*, CUtensorMapDataType, cuuint32_t, void*, const cuuint64_t*, const cuuint64_t*,
                                  const cuuint32_t*, const cuuint32_t*, CUtensorMapInterleave, CUtensorMapSwizzle,
                                  CUtensorMapL2promotion, CUtensorMapFloatOOBfill);

static bool encode_weight_map(EncodeTiledFn fn, CUtensorMap* map, const void* base, int rows) {
    const cuuint64_t dims[2] = {(cuuint64_t)kD, (cuuint64_t)rows};
    const cuuint64_t strides[1] = {(cuuint64_t)kD * 2};
    const cuuint32_t box[2] = {32, 128};
    const cuuint32_t estr[2] = {1, 1};
    return fn(map, CU_TENSOR_MAP_DATA_TYPE_BFLOAT16, 2, const_cast<void*>(base), dims, strides, box, estr,
              CU_TENSOR_MAP_INTERLEAVE_NONE, CU_TENSOR_MAP_SWIZZLE_64B, CU_TENSOR_MAP_L2_PROMOTION_L2_256B,
              CU_TENSOR_MAP_FLOAT_OOB_FILL_NONE) == CUDA_SUCCESS;
}

extern "C" void kernel_launch(void* const* d_in, const int* in_sizes, int n_in, void* d_out, int out_size) {
    (void)in_sizes; (void)n_in; (void)out_size;
    const __nv_bfloat16* x  = (const __nv_bfloat16*)d_in[0];
    const __nv_bfloat16* kc = (const __nv_bfloat16*)d_in[1];
    const __nv_bfloat16* vc = (const __nv_bfloat16*)d_in[2];
    const __nv_bfloat16* wq = (const __nv_bfloat16*)d_in[3];
    const __nv_bfloat16* wo = (const __nv_bfloat16*)d_in[4];
    const __nv_bfloat16* w1 = (const __nv_bfloat16*)d_in[6];
    const __nv_bfloat16* b1 = (const __nv_bfloat16*)d_in[7];
    const __nv_bfloat16* w2 = (const __nv_bfloat16*)d_in[8];
    const __nv_bfloat16* b2 = (const __nv_bfloat16*)d_in[9];
    __nv_bfloat16* out = (__nv_bfloat16*)d_out;

    static int grid = 0;
    static EncodeTiledFn encode = nullptr;
    static CUtensorMap map_wo, map_w2;
    static const void* cached_wo = nullptr;
    static const void* cached_w2 = nullptr;
    if (grid == 0) {
        int dev = 0, sms = 0;
        cudaGetDevice(&dev);
        cudaDeviceGetAttribute(&sms, cudaDevAttrMultiProcessorCount, dev);
        cudaFuncSetAttribute(fused_decode_kernel, cudaFuncAttributeMaxDynamicSharedMemorySize, kSmemBytes);
        void* fn = nullptr;
        cudaDriverEntryPointQueryResult qres;
        cudaGetDriverEntryPoint("cuTensorMapEncodeTiled", &fn, cudaEnableDefault, &qres);
        encode = (EncodeTiledFn)fn;
        grid = sms > 0 ? sms : 1;
    }
    if (encode == nullptr) return;
    if (cached_wo != (const void*)wo) { encode_weight_map(encode, &map_wo, wo, kH * kDH); cached_wo = wo; }
    if (cached_w2 != (const void*)w2) { encode_weight_map(encode, &map_w2, w2, kF); cached_w2 = w2; }
    fused_decode_kernel<<<grid, kThreads, kSmemBytes>>>(x, kc, vc, wq, w1, b1, b2, out, map_wo, map_w2);
}
```

```cpp
#include <cuda_runtime.h>
#include <cuda.h>
#include <cuda_bf16.h>
#include <stdint.h>
#include <limits.h>

namespace {

constexpr int kB = 8, kD = 512, kH = 32, kSK = 4096, kDH = 128, kF = 1792;
constexpr int kPairs = kB * kH;
constexpr int kTileKeys = 128;
constexpr int kTilesPerPair = kSK / kTileKeys;
constexpr int kTileBytes = kTileKeys * kDH * 2;
constexpr int kAuxBytes = 2048;
constexpr int kSlotBytes = kTileBytes + kAuxBytes;
constexpr int kSlots = 6;
constexpr int kLag = 256;
constexpr int kStreamUnits = 2 * kPairs * kTilesPerPair;
constexpr int kFSlices = kF / 128;
constexpr int kSlices = kH + kFSlices;
constexpr int kAttnUnits = kH * 4;
constexpr int kFfnUnits = kFSlices * 4;
constexpr int kQTasks = (kH * kDH) / 32;
constexpr int kFTasks = kF / 16;
constexpr int kFinalTasks = kB * kD / 32;
constexpr int kPieceBytes = kTileBytes / 4;
constexpr int kWin = 6;
constexpr int kEarly = 6;
constexpr int kFast = 2;
constexpr int kStatic = kSlots - 1;
constexpr int kProjWait = 2;
constexpr int kFfnPos = 2048;
constexpr int kTickets = kStreamUnits + kFfnUnits;
constexpr int kInStride = 272;
constexpr int kConsumerThreads = 128;
constexpr int kThreads = 160;
constexpr int kXnStride = 1040;

constexpr uint32_t kTypeK = 0, kTypeV = 1, kTypeP = 2, kTypeSignal = 3, kTypeF = 4;
constexpr uint32_t kDescNoAux = 1u << 16;
constexpr int kMaxGrid = 160;
static_assert(kStatic * kMaxGrid <= kLag * kTilesPerPair, "static units must be K units");
static_assert(kStatic * kMaxGrid <= kFfnPos, "static units precede the FFN units");

constexpr int kMiscOff = kSlots * kSlotBytes;
constexpr int kOffFull = kMiscOff;
constexpr int kOffEmpty = kOffFull + 256;
constexpr int kOffDesc = kOffEmpty + 64;
constexpr int kOffEpochBar = kOffDesc + 32;
constexpr int kOffEpoch = kOffDesc + 40;
constexpr int kOffL = kOffDesc + 64;
constexpr int kOffRed = kOffL + 64;
constexpr int kOffStamp = kOffRed + 4096;
constexpr int kOffXn = kOffStamp + 128;
constexpr int kOffPart = kOffXn + kB * kXnStride;
constexpr int kSmemUsed = kOffPart + 4096;
constexpr int kSmemBytes = kSmemUsed + 1024;
static_assert(kSmemBytes <= 232448, "shared memory budget");
static_assert(kSlots * 4 * 8 <= 256, "barrier area");
static_assert(kEarly <= kWin && kEarly <= kStatic * 4 && 1 + kStatic == kSlots, "start-up configuration");

constexpr unsigned kSpinLimit = 1u << 24;

struct State {
    unsigned long long ticket;
    unsigned pad0[30];
    unsigned exhausted;
    unsigned pad1[31];
};

__device__ __align__(128) State g_state;
__device__ __align__(128) uint2 g_q[kPairs * 64];
__device__ __align__(128) uint2 g_h[kB * (kF / 2)];
__device__ __align__(128) uint32_t g_score[kPairs * kSK];
__device__ __align__(128) uint32_t g_max[kPairs * 128];
__device__ __align__(128) float g_oacc[kPairs * kDH * 2];
__device__ __align__(128) float g_lacc[kPairs * 32];
__device__ __align__(128) uint2 g_contrib[kSlices * kB * kD];

#define STAMP(i) do { } while (0)

__device__ __forceinline__ uint32_t smem_u32(const void* p) { return (uint32_t)__cvta_generic_to_shared(p); }

__device__ __forceinline__ void mbar_init(uint32_t bar, uint32_t cnt) {
    asm volatile("mbarrier.init.shared::cta.b64 [%0], %1;" ::"r"(bar), "r"(cnt) : "memory");
}
__device__ __forceinline__ void mbar_expect_tx(uint32_t bar, uint32_t bytes) {
    asm volatile("mbarrier.arrive.expect_tx.shared::cta.b64 _, [%0], %1;" ::"r"(bar), "r"(bytes) : "memory");
}
__device__ __forceinline__ void mbar_arrive(uint32_t bar) {
    asm volatile("mbarrier.arrive.shared::cta.b64 _, [%0];" ::"r"(bar) : "memory");
}
__device__ __forceinline__ bool mbar_try(uint32_t bar, uint32_t parity) {
    uint32_t ok;
    asm volatile(
        "{\n.reg .pred p;\n"
        "mbarrier.try_wait.parity.shared::cta.b64 p, [%1], %2;\n"
        "selp.u32 %0, 1, 0, p;\n}"
        : "=r"(ok) : "r"(bar), "r"(parity) : "memory");
    return ok != 0;
}
__device__ __forceinline__ void mbar_wait(uint32_t bar, uint32_t parity) {
    unsigned n = 0;
    while (!mbar_try(bar, parity)) {
        if (++n > kSpinLimit) __trap();
    }
}
__device__ __forceinline__ void bulk_load(uint32_t dst, const void* src, uint32_t bytes, uint32_t bar) {
    asm volatile("cp.async.bulk.shared::cluster.global.mbarrier::complete_tx::bytes [%0], [%1], %2, [%3];"
                 ::"r"(dst), "l"(src), "r"(bytes), "r"(bar) : "memory");
}
__device__ __forceinline__ void bulk_load_hint(uint32_t dst, const void* src, uint32_t bytes, uint32_t bar, uint64_t pol) {
    asm volatile("cp.async.bulk.shared::cluster.global.mbarrier::complete_tx::bytes.L2::cache_hint [%0], [%1], %2, [%3], %4;"
                 ::"r"(dst), "l"(src), "r"(bytes), "r"(bar), "l"(pol) : "memory");
}
__device__ __forceinline__ void tma_load_2d(uint32_t dst, const CUtensorMap* map, int c0, int c1, uint32_t bar) {
    asm volatile("cp.async.bulk.tensor.2d.shared::cluster.global.mbarrier::complete_tx::bytes [%0], [%1, {%3, %4}], [%2];"
                 ::"r"(dst), "l"(map), "r"(bar), "r"(c0), "r"(c1) : "memory");
}
__device__ __forceinline__ void cp_async16(uint32_t dst, const void* src) {
    asm volatile("cp.async.cg.shared.global [%0], [%1], 16;" ::"r"(dst), "l"(src) : "memory");
}
__device__ __forceinline__ void cp_async16_pf(uint32_t dst, const void* src) {
    asm volatile("cp.async.cg.shared.global.L2::256B [%0], [%1], 16;" ::"r"(dst), "l"(src) : "memory");
}
__device__ __forceinline__ void cp_async_commit() { asm volatile("cp.async.commit_group;" ::: "memory"); }
template <int N>
__device__ __forceinline__ void cp_async_wait() { asm volatile("cp.async.wait_group %0;" ::"n"(N) : "memory"); }

__device__ __forceinline__ void named_bar(int id, int n) { asm volatile("bar.sync %0, %1;" ::"r"(id), "r"(n) : "memory"); }

__device__ __forceinline__ void ldsm4(uint32_t (&r)[4], uint32_t addr) {
    asm volatile("ldmatrix.sync.aligned.m8n8.x4.shared.b16 {%0,%1,%2,%3}, [%4];"
                 : "=r"(r[0]), "=r"(r[1]), "=r"(r[2]), "=r"(r[3]) : "r"(addr) : "memory");
}
__device__ __forceinline__ void ldsm4t(uint32_t (&r)[4], uint32_t addr) {
    asm volatile("ldmatrix.sync.aligned.m8n8.x4.trans.shared.b16 {%0,%1,%2,%3}, [%4];"
                 : "=r"(r[0]), "=r"(r[1]), "=r"(r[2]), "=r"(r[3]) : "r"(addr) : "memory");
}
__device__ __forceinline__ void mma16816(float (&c)[4], const uint32_t (&a)[4], uint32_t b0, uint32_t b1) {
    asm volatile("mma.sync.aligned.m16n8k16.row.col.f32.bf16.bf16.f32 {%0,%1,%2,%3}, {%4,%5,%6,%7}, {%8,%9}, {%0,%1,%2,%3};"
                 : "+f"(c[0]), "+f"(c[1]), "+f"(c[2]), "+f"(c[3])
                 : "r"(a[0]), "r"(a[1]), "r"(a[2]), "r"(a[3]), "r"(b0), "r"(b1));
}
__device__ __forceinline__ uint32_t lds32(uint32_t a) { uint32_t v; asm volatile("ld.shared.u32 %0, [%1];" : "=r"(v) : "r"(a) : "memory"); return v; }
__device__ __forceinline__ uint2 lds64(uint32_t a) { uint2 v; asm volatile("ld.shared.v2.u32 {%0,%1}, [%2];" : "=r"(v.x), "=r"(v.y) : "r"(a) : "memory"); return v; }
__device__ __forceinline__ uint4 lds128(uint32_t a) { uint4 v; asm volatile("ld.shared.v4.u32 {%0,%1,%2,%3}, [%4];" : "=r"(v.x), "=r"(v.y), "=r"(v.z), "=r"(v.w) : "r"(a) : "memory"); return v; }
__device__ __forceinline__ float lds_f(uint32_t a) { float v; asm volatile("ld.shared.f32 %0, [%1];" : "=f"(v) : "r"(a) : "memory"); return v; }
__device__ __forceinline__ void sts32(uint32_t a, uint32_t v) { asm volatile("st.shared.u32 [%0], %1;" ::"r"(a), "r"(v) : "memory"); }
__device__ __forceinline__ void sts_f(uint32_t a, float v) { asm volatile("st.shared.f32 [%0], %1;" ::"r"(a), "f"(v) : "memory"); }
__device__ __forceinline__ void sts128(uint32_t a, uint4 v) { asm volatile("st.shared.v4.u32 [%0], {%1,%2,%3,%4};" ::"r"(a), "r"(v.x), "r"(v.y), "r"(v.z), "r"(v.w) : "memory"); }

__device__ __forceinline__ uint2 ld_rlx64(const uint2* p) {
    unsigned long long v;
    asm volatile("ld.relaxed.gpu.global.b64 %0, [%1];" : "=l"(v) : "l"(p) : "memory");
    return make_uint2((uint32_t)v, (uint32_t)(v >> 32));
}
__device__ __forceinline__ void st_rlx64(uint2* p, uint32_t lo, uint32_t hi) {
    unsigned long long v = ((unsigned long long)hi << 32) | lo;
    asm volatile("st.relaxed.gpu.global.b64 [%0], %1;" ::"l"(p), "l"(v) : "memory");
}
__device__ __forceinline__ uint4 ld_rlx128(const uint32_t* p) {
    uint4 v;
    asm volatile("ld.relaxed.gpu.global.v4.u32 {%0,%1,%2,%3}, [%4];" : "=r"(v.x), "=r"(v.y), "=r"(v.z), "=r"(v.w) : "l"(p) : "memory");
    return v;
}
__device__ __forceinline__ void st_rlx128(uint32_t* p, uint4 v) {
    asm volatile("st.relaxed.gpu.global.v4.u32 [%0], {%1,%2,%3,%4};" ::"l"(p), "r"(v.x), "r"(v.y), "r"(v.z), "r"(v.w) : "memory");
}
__device__ __forceinline__ void st_rlx32(uint32_t* p, uint32_t v) {
    asm volatile("st.relaxed.gpu.global.u32 [%0], %1;" ::"l"(p), "r"(v) : "memory");
}
__device__ __forceinline__ float4 ld_rlx_f4(const float* p) {
    float4 v;
    asm volatile("ld.relaxed.gpu.global.v4.f32 {%0,%1,%2,%3}, [%4];" : "=f"(v.x), "=f"(v.y), "=f"(v.z), "=f"(v.w) : "l"(p) : "memory");
    return v;
}
__device__ __forceinline__ uint32_t ldg_u32(const void* p) { uint32_t v; asm volatile("ld.global.nc.u32 %0, [%1];" : "=r"(v) : "l"(p)); return v; }
__device__ __forceinline__ uint32_t ldg_u16(const void* p) { uint16_t v; asm volatile("ld.global.nc.u16 %0, [%1];" : "=h"(v) : "l"(p)); return v; }
__device__ __forceinline__ void prefetch_l2(const void* p) { asm volatile("prefetch.global.L2 [%0];" ::"l"(p)); }
__device__ __forceinline__ float2 ld_rlx_f2(const float* p) {
    float2 v;
    asm volatile("ld.relaxed.gpu.global.v2.f32 {%0,%1}, [%2];" : "=f"(v.x), "=f"(v.y) : "l"(p) : "memory");
    return v;
}
__device__ __forceinline__ void red_add_2f32(float* p, float a, float b) {
    asm volatile("red.relaxed.gpu.global.add.v2.f32 [%0], {%1, %2};" ::"l"(p), "f"(a), "f"(b) : "memory");
}
__device__ __forceinline__ unsigned long long atom_inc_u64(unsigned long long* p) {
    unsigned long long r;
    asm volatile("{\n.reg .u32 l;\n.reg .u64 v;\nmov.u32 l, %%laneid;\nadd.u32 l, l, 1;\ncvt.u64.u32 v, l;\n"
                 "atom.relaxed.gpu.global.add.u64 %0, [%1], v;\n}" : "=l"(r) : "l"(p) : "memory");
    return r;
}
__device__ __forceinline__ unsigned atom_inc_u32(unsigned* p) {
    unsigned r;
    asm volatile("{\n.reg .u32 l;\nmov.u32 l, %%laneid;\nadd.u32 l, l, 1;\n"
                 "atom.relaxed.gpu.global.add.u32 %0, [%1], l;\n}" : "=r"(r) : "l"(p) : "memory");
    return r;
}

__device__ __forceinline__ float bfr(float f) { return __bfloat162float(__float2bfloat16_rn(f)); }
__device__ __forceinline__ uint32_t bf_bits(float f) { return (uint32_t)__bfloat16_as_ushort(__float2bfloat16_rn(f)); }
__device__ __forceinline__ uint32_t pack_bf2(float lo, float hi) {
    __nv_bfloat162 v = __floats2bfloat162_rn(lo, hi);
    return *reinterpret_cast<uint32_t*>(&v);
}
__device__ __forceinline__ float bf_lo(uint32_t w) { return __uint_as_float(w << 16); }
__device__ __forceinline__ float bf_hi(uint32_t w) { return __uint_as_float(w & 0xffff0000u); }
__device__ __forceinline__ int ord(uint32_t bits) { int i = (int)bits; return i ^ ((i >> 31) & 0x7fffffff); }
__device__ __forceinline__ float ex2(float x) { float y; asm("ex2.approx.ftz.f32 %0, %1;" : "=f"(y) : "f"(x)); return y; }

__device__ __forceinline__ void decode_unit(uint32_t u, uint32_t& type, uint32_t& pair, uint32_t& tile) {
    const uint32_t blk = u >> 5;
    tile = u & 31;
    if (blk < (uint32_t)kLag) {
        type = kTypeK; pair = blk;
    } else if (blk < (uint32_t)(2 * kPairs - kLag)) {
        const uint32_t g = blk - kLag;
        if (g & 1) { type = kTypeK; pair = kLag + (g >> 1); }
        else       { type = kTypeV; pair = g >> 1; }
    } else {
        type = kTypeV; pair = blk - kPairs;
    }
}

__global__ void __launch_bounds__(kThreads, 1)
fused_decode_kernel(const __nv_bfloat16* __restrict__ x, const __nv_bfloat16* __restrict__ kc,
                    const __nv_bfloat16* __restrict__ vc, const __nv_bfloat16* __restrict__ wq,
                    const __nv_bfloat16* __restrict__ w1, const __nv_bfloat16* __restrict__ b1,
                    const __nv_bfloat16* __restrict__ b2, __nv_bfloat16* __restrict__ out,
                    const __grid_constant__ CUtensorMap map_wo, const __grid_constant__ CUtensorMap map_w2) {
    extern __shared__ uint8_t smem_raw[];
    const uint32_t sbase = (smem_u32(smem_raw) + 1023u) & ~1023u;
    const int tid = threadIdx.x;
    const int warp = tid >> 5;
    const int lane = tid & 31;
    const uint32_t G = gridDim.x;
    const uint32_t cta = blockIdx.x;

    uint64_t pol = 0;
    if (tid == kConsumerThreads) {
        STAMP(0);
        for (uint32_t c = cta; c < 128; c += G)
            asm volatile("cp.async.bulk.prefetch.L2.global [%0], %1;" ::"l"(reinterpret_cast<const char*>(wq) + (size_t)c * 32768), "r"(32768) : "memory");
        for (uint32_t c = cta; c < 112; c += G)
            asm volatile("cp.async.bulk.prefetch.L2.global [%0], %1;" ::"l"(reinterpret_cast<const char*>(w1) + (size_t)c * 16384), "r"(16384) : "memory");
        asm volatile("createpolicy.fractional.L2::evict_first.b64 %0, 1.0;" : "=l"(pol));
#pragma unroll 1
        for (int i = 0; i < kSlots * 4; i++) mbar_init(sbase + kOffFull + i * 8, 1);
        asm volatile("fence.mbarrier_init.release.cluster;" ::: "memory");
#pragma unroll 1
        for (int i = 0; i < kFast; i++) {
            const uint32_t full = sbase + kOffFull + (4 + i) * 8;
            mbar_expect_tx(full, kPieceBytes);
            bulk_load_hint(sbase + (1 + (i >> 2)) * kSlotBytes + (i & 3) * kPieceBytes,
                           kc + ((size_t)(cta + (i >> 2) * G) * kTileKeys + (i & 3) * 32) * kDH, kPieceBytes, full, pol);
        }
    }

    if (warp == 4) {
        uint32_t slot = 1, phase = 0;
        int tc = 4 - kWin;
        uint32_t tb = (uint32_t)((4 - kWin + 4 * kSlots) % (4 * kSlots)), tphase = 0;
        auto window = [&](bool wait = true) {
            if (wait && tc >= 4) mbar_wait(sbase + kOffFull + tb * 8, tphase);
            ++tc;
            if (++tb == 4u * kSlots) { tb = 0; if (tc > 0) tphase ^= 1; }
        };
        auto wait_empty = [&]() { mbar_wait(sbase + kOffEmpty + slot * 8, phase ^ 1); };
        auto advance = [&]() { if (++slot == (uint32_t)kSlots) { slot = 0; phase ^= 1; } };
        auto issue_piece = [&](uint32_t type, uint32_t pair, uint32_t tile, int p) {
            window();
            const uint32_t full = sbase + kOffFull + (slot * 4 + p) * 8;
            const uint32_t dst = sbase + slot * kSlotBytes;
            const size_t off = ((size_t)pair * kSK + (size_t)tile * kTileKeys + p * 32) * kDH;
            const __nv_bfloat16* src = (type == kTypeK ? kc : vc) + off;
            if (p == 0) {
                sts32(sbase + kOffDesc + slot * 4, type | (pair << 3) | (tile << 11));
                if (type == kTypeK) {
                    mbar_expect_tx(full, kPieceBytes + 512);
                    bulk_load(dst + kTileBytes, g_q + pair * 64, 512, full);
                } else {
                    mbar_expect_tx(full, kPieceBytes + 1024);
                    bulk_load(dst + kTileBytes, g_score + pair * kSK + tile * kTileKeys, 512, full);
                    bulk_load(dst + kTileBytes + 512, g_max + pair * 128, 512, full);
                }
            } else {
                mbar_expect_tx(full, kPieceBytes);
            }
            bulk_load_hint(dst + p * kPieceBytes, src, kPieceBytes, full, pol);
        };
        unsigned long long ticket = 0;
        if (lane == 0) {
            for (int i = 0; i < kSlots; i++) mbar_init(sbase + kOffEmpty + i * 8, 4);
            mbar_init(sbase + kOffEpochBar, 1);
            asm volatile("fence.mbarrier_init.release.cluster;" ::: "memory");
            for (int i = 0; i < 4; i++) mbar_arrive(sbase + kOffFull + i * 8);
            for (int k = 0; k < kStatic; k++) {
                const uint32_t u = cta + k * G;
                sts32(sbase + kOffDesc + (1 + k) * 4, kTypeK | ((u >> 5) << 3) | ((u & 31) << 11) | kDescNoAux);
            }
            ticket = atom_inc_u64(&g_state.ticket);
        }
        named_bar(2, kThreads);
        if (lane == 0) {
#pragma unroll 1
            for (int i = kFast; i < kEarly; i++) {
                const uint32_t full = sbase + kOffFull + (4 + i) * 8;
                mbar_expect_tx(full, kPieceBytes);
                bulk_load_hint(sbase + (1 + (i >> 2)) * kSlotBytes + (i & 3) * kPieceBytes,
                               kc + ((size_t)(cta + (i >> 2) * G) * kTileKeys + (i & 3) * 32) * kDH, kPieceBytes, full, pol);
            }
            sts32(sbase + kOffEpoch, (uint32_t)(ticket >> 32));
            mbar_arrive(sbase + kOffEpochBar);
            asm volatile("prefetch.tensormap [%0];" ::"l"(&map_wo) : "memory");
            asm volatile("prefetch.tensormap [%0];" ::"l"(&map_w2) : "memory");
        }
        __syncwarp();
#pragma unroll 1
        for (int i = 0; i < kStatic * 4; i++) {
            if (i >= kEarly) {
                window(true);
                if (lane == 0) {
                    const uint32_t full = sbase + kOffFull + (4 + i) * 8;
                    mbar_expect_tx(full, kPieceBytes);
                    bulk_load_hint(sbase + (1 + (i >> 2)) * kSlotBytes + (i & 3) * kPieceBytes,
                                   kc + ((size_t)(cta + (i >> 2) * G) * kTileKeys + (i & 3) * 32) * kDH, kPieceBytes, full, pol);
                }
            } else {
                window(false);
            }
        }
        slot = (1 + kStatic) % kSlots;
        phase = (1 + kStatic) / kSlots;
        for (uint32_t ft = cta; ft < (uint32_t)kFTasks; ft += G) {
            wait_empty();
#pragma unroll 1
            for (int p = 0; p < 4; p++) {
                window();
                const uint32_t full = sbase + kOffFull + (slot * 4 + p) * 8;
                const __nv_bfloat16* src = w1 + ft * 16 + (size_t)(p * 128 + (lane >> 1)) * kF + (lane & 1) * 8;
                const uint32_t dst = sbase + slot * kSlotBytes + (p * 128 + (lane >> 1)) * 32 + (((lane & 1) ^ ((lane >> 3) & 1)) << 4);
#pragma unroll
                for (int i = 0; i < 8; i++) cp_async16_pf(dst + i * 512, src + (size_t)i * 16 * kF);
                asm volatile("cp.async.mbarrier.arrive.shared::cta.b64 [%0];" ::"r"(full) : "memory");
                __syncwarp();
                if (lane == 0) {
                    if (p == 0) sts32(sbase + kOffDesc + slot * 4, kTypeF | (ft << 3));
                    mbar_arrive(full);
                }
            }
            advance();
        }
        auto issue_proj = [&](uint32_t slice, uint32_t quarter, bool use_window) {
            const uint32_t dst = sbase + slot * kSlotBytes;
            wait_empty();
            const CUtensorMap* map = (slice < (uint32_t)kH) ? &map_wo : &map_w2;
            const int row = (int)((slice < (uint32_t)kH) ? slice : slice - kH) * 128;
            sts32(sbase + kOffDesc + slot * 4, kTypeP | (slice << 3) | (quarter << 11));
            for (int p = 0; p < 4; p++) {
                const uint32_t full = sbase + kOffFull + (slot * 4 + p) * 8;
                if (use_window) window();
                mbar_expect_tx(full, kPieceBytes);
                tma_load_2d(dst + p * kPieceBytes, map, (int)quarter * 128 + p * 32, row, full);
            }
            advance();
        };
        if (lane == 0) {
            uint32_t pending = (uint32_t)ticket;
            uint32_t u = pending + kStatic * G;
            while (u < (uint32_t)kTickets) {
                if (u >= (uint32_t)kFfnPos && u < (uint32_t)(kFfnPos + kFfnUnits)) {
                    pending = (uint32_t)atom_inc_u64(&g_state.ticket);
                    const uint32_t f = u - kFfnPos;
                    issue_proj(kH + (f >> 2), f & 3, true);
                } else {
                    uint32_t type, pair, tile;
                    decode_unit(u < (uint32_t)kFfnPos ? u : u - kFfnUnits, type, pair, tile);
                    wait_empty();
                    issue_piece(type, pair, tile, 0);
                    pending = (uint32_t)atom_inc_u64(&g_state.ticket);
#pragma unroll 1
                    for (int p = 1; p < 4; p++) issue_piece(type, pair, tile, p);
                    advance();
                }
                u = pending + kStatic * G;
            }
        }
        __syncwarp();
        if (cta < (uint32_t)kAttnUnits) {
            prefetch_l2(g_oacc + ((lane >> 2) * kH + (cta >> 2)) * (kDH * 2) + (lane & 3) * 64);
            prefetch_l2(g_oacc + ((lane >> 2) * kH + (cta >> 2)) * (kDH * 2) + (lane & 3) * 64 + 32);
            if (lane < 8) prefetch_l2(g_lacc + (lane * kH + (cta >> 2)) * 32);
            if (lane < 2 * kFSlices) prefetch_l2(g_contrib + (size_t)(kH + (lane >> 1)) * (kB * kD) + cta * 32 + (lane & 1) * 16);
        }
        for (uint32_t un = cta; un < (uint32_t)kAttnUnits; un += G) {
            uint2* cp = g_contrib + (size_t)(un >> 2) * (kB * kD) + (un & 3) * 128 + (lane >> 2) * kD + (lane & 3) * 2;
#pragma unroll 4
            for (int i = 0; i < 16; i++) st_rlx128(reinterpret_cast<uint32_t*>(cp + i * 8), make_uint4(0u, 0u, 0u, 0u));
        }
        __syncwarp();
        if (lane != 0) return;
        const uint32_t lslot = (slot == 0) ? kSlots - 1 : slot - 1;
        const uint32_t lphase = (slot == 0) ? phase ^ 1 : phase;
        wait_empty();
        sts32(sbase + kOffDesc + slot * 4, kTypeSignal);
        for (int p = 0; p < 4; p++) mbar_arrive(sbase + kOffFull + (slot * 4 + p) * 8);
        advance();
        for (int p = 0; p < kProjWait; p++) mbar_wait(sbase + kOffFull + (lslot * 4 + p) * 8, lphase);
        for (uint32_t a = cta; a < (uint32_t)kAttnUnits; a += G) issue_proj(a >> 2, a & 3, false);
        if (atom_inc_u32(&g_state.exhausted) == G - 1) {
            g_state.exhausted = 0;
            g_state.ticket = ((ticket >> 32) + 1) << 32;
        }
        return;
    }

    const int g = lane >> 2;
    const int j = lane & 3;
    const int mi = lane >> 3;
    const int r = lane & 7;
    const bool diag = (j == (g >> 1));

    const uint32_t s_wq = sbase;
    const uint32_t s_xn = sbase + kOffXn;
    const uint32_t s_part = sbase + kOffPart;

    auto load_wq = [&](uint32_t task) {
        const __nv_bfloat16* src = wq + task * 32 + (size_t)(tid >> 2) * (kH * kDH) + (tid & 3) * 8;
        const uint32_t dst = s_wq + (tid >> 2) * 64 + (((tid & 3) ^ ((tid >> 3) & 3)) << 4);
#pragma unroll 4
        for (int i = 0; i < 16; i++) cp_async16_pf(dst + i * 2048, src + (size_t)i * 32 * (kH * kDH));
    };
#pragma unroll
    for (int i = 0; i < 4; i++) {
        const int row = warp * 2 + (i >> 1), ch = lane + (i & 1) * 32;
        cp_async16(s_xn + row * kXnStride + ch * 16, x + row * kD + ch * 8);
    }
    cp_async_commit();
    for (uint32_t qt = cta; qt < (uint32_t)kQTasks; qt += G)
        st_rlx64(g_q + ((tid >> 4) * kH + (qt >> 2)) * 64 + (qt & 3) * 16 + (tid & 15), 0u, 0u);
    uint32_t b1raw = 0, fxraw = 0, fb2raw = 0;
    if (tid < 64 && cta < (uint32_t)kFTasks) b1raw = ldg_u32(b1 + cta * 16 + 2 * (tid & 7));
    if (cta < (uint32_t)kFinalTasks) {
        fxraw = ldg_u16(x + cta * 32 + warp * 8 + (lane & 7));
        fb2raw = ldg_u16(b2 + ((cta * 32 + warp * 8 + (lane & 7)) & (kD - 1)));
    }
    named_bar(2, kThreads);

    cp_async_wait<0>();
    if (cta < (uint32_t)kQTasks) load_wq(cta);
    cp_async_commit();
    __syncwarp();
    if (tid == 0) STAMP(10);
    {
        float v[2][16];
        float s[2], q2[2];
#pragma unroll
        for (int rr = 0; rr < 2; rr++) {
            const uint32_t a = s_xn + (warp * 2 + rr) * kXnStride + lane * 32;
            const uint4 x0 = lds128(a), x1 = lds128(a + 16);
            const uint32_t w[8] = {x0.x, x0.y, x0.z, x0.w, x1.x, x1.y, x1.z, x1.w};
#pragma unroll
            for (int i = 0; i < 8; i++) { v[rr][2 * i] = bf_lo(w[i]); v[rr][2 * i + 1] = bf_hi(w[i]); }
            float s0 = 0.f, s1 = 0.f, s2 = 0.f, s3 = 0.f;
#pragma unroll
            for (int i = 0; i < 4; i++) { s0 += v[rr][i]; s1 += v[rr][4 + i]; s2 += v[rr][8 + i]; s3 += v[rr][12 + i]; }
            s[rr] = (s0 + s1) + (s2 + s3);
        }
#pragma unroll
        for (int o = 16; o > 0; o >>= 1) {
            s[0] += __shfl_xor_sync(0xffffffffu, s[0], o);
            s[1] += __shfl_xor_sync(0xffffffffu, s[1], o);
        }
#pragma unroll
        for (int rr = 0; rr < 2; rr++) {
            const float mean = s[rr] * (1.0f / kD);
            s[rr] = mean;
            float t0 = 0.f, t1 = 0.f, t2 = 0.f, t3 = 0.f;
#pragma unroll
            for (int i = 0; i < 4; i++) {
                const float d0 = v[rr][i] - mean, d1 = v[rr][4 + i] - mean, d2 = v[rr][8 + i] - mean, d3 = v[rr][12 + i] - mean;
                t0 += d0 * d0; t1 += d1 * d1; t2 += d2 * d2; t3 += d3 * d3;
            }
            q2[rr] = (t0 + t1) + (t2 + t3);
        }
#pragma unroll
        for (int o = 16; o > 0; o >>= 1) {
            q2[0] += __shfl_xor_sync(0xffffffffu, q2[0], o);
            q2[1] += __shfl_xor_sync(0xffffffffu, q2[1], o);
        }
#pragma unroll
        for (int rr = 0; rr < 2; rr++) {
            const float mb = bfr(s[rr]);
            const float vb = bfr(q2[rr] * (1.0f / kD));
            const float sd = bfr(__fsqrt_rn(bfr(vb + 1e-5f)));
            const float rs = __frcp_rn(sd);
            uint32_t o[8];
#pragma unroll
            for (int i = 0; i < 8; i++) o[i] = pack_bf2(bfr(v[rr][2 * i] - mb) * rs, bfr(v[rr][2 * i + 1] - mb) * rs);
            const uint32_t a = s_xn + (warp * 2 + rr) * kXnStride + lane * 32;
            sts128(a, make_uint4(o[0], o[1], o[2], o[3]));
            sts128(a + 16, make_uint4(o[4], o[5], o[6], o[7]));
        }
    }

    uint32_t epoch = 0, tag32 = 0;
#pragma unroll 1
    for (uint32_t qt = cta; qt < (uint32_t)kQTasks; qt += G) {
        if (qt != cta) {
            named_bar(1, kConsumerThreads);
            load_wq(qt);
            cp_async_commit();
        }
        cp_async_wait<0>();
        named_bar(1, kConsumerThreads);
        float acc[2][2][4] = {};
        const uint32_t a0 = s_wq + (warp * 128 + (mi >> 1) * 8 + r) * 64 + (((mi & 1) ^ ((r >> 1) & 3)) << 4);
        const uint32_t b0 = s_xn + g * kXnStride + (warp * 128 + 2 * j) * 2;
#pragma unroll
        for (int ks = 0; ks < 8; ks++) {
            const uint32_t bx0 = lds32(b0 + ks * 32), bx1 = lds32(b0 + ks * 32 + 16);
#pragma unroll
            for (int mt = 0; mt < 2; mt++) {
                uint32_t a[4];
                ldsm4t(a, (a0 + ks * 1024) ^ (mt << 5));
                mma16816(acc[mt][ks & 1], a, bx0, bx1);
            }
        }
#pragma unroll
        for (int mt = 0; mt < 2; mt++) {
            const uint32_t p = s_part + (warp * 32 + mt * 16 + g) * 32 + j * 8;
            sts_f(p, acc[mt][0][0] + acc[mt][1][0]); sts_f(p + 4, acc[mt][0][1] + acc[mt][1][1]);
            sts_f(p + 256, acc[mt][0][2] + acc[mt][1][2]); sts_f(p + 260, acc[mt][0][3] + acc[mt][1][3]);
        }
        named_bar(1, kConsumerThreads);
        mbar_wait(sbase + kOffEpochBar, 0);
        tag32 = lds32(sbase + kOffEpoch) + 1;
        const int b = tid >> 4, cp = tid & 15;
        float v0 = 0.f, v1 = 0.f;
#pragma unroll
        for (int w = 0; w < 4; w++) {
            v0 += lds_f(s_part + (w * 32 + 2 * cp) * 32 + b * 4);
            v1 += lds_f(s_part + (w * 32 + 2 * cp + 1) * 32 + b * 4);
        }
        st_rlx64(g_q + (b * kH + (qt >> 2)) * 64 + (qt & 3) * 16 + cp, pack_bf2(v0, v1), tag32);
    }
    if (tid == 0) STAMP(1);
    cp_async_wait<0>();
    asm volatile("fence.proxy.async.shared::cta;" ::: "memory");
    named_bar(1, kConsumerThreads);
    if (lane == 0) mbar_arrive(sbase + kOffEmpty + 0);
    mbar_wait(sbase + kOffEpochBar, 0);
    epoch = lds32(sbase + kOffEpoch);
    tag32 = epoch + 1;
    const uint32_t tag16 = (epoch % 65535u) + 1u;

    const uint32_t k_lane_off = (uint32_t)(warp * 32 + (mi & 1) * 8 + r) * 256u + (uint32_t)(((r & 6) | ((mi >> 1) ^ (r & 1))) << 4);
    const uint32_t v_lane_off = (uint32_t)(warp * 32 + (mi >> 1) * 8 + r) * 256u + (uint32_t)(((r & 6) | ((mi & 1) ^ (r & 1))) << 4);
    constexpr float kScale = 0.08838834764831845f;
    constexpr float kLog2e = 1.4426950408889634f;

    uint32_t slot = 1, phase = 0, rbuf = 0;
    float* const oacc = g_oacc;
    float* const lacc = g_lacc;
    const float cnt_base = (float)((epoch & 1023u) * 64u);
    const float cnt_full = cnt_base + (float)kTilesPerPair;
    auto stage_input = [&](uint32_t slice) {
        const int sb = tid >> 4, sc = tid & 15;
        uint4 inw;
        if (slice >= (uint32_t)kH) {
            const uint2* hp = g_h + sb * (kF / 2) + (slice - kH) * 64 + sc * 4;
            unsigned it = 0;
            bool ok;
            do {
                const uint2 w0 = ld_rlx64(hp), w1_ = ld_rlx64(hp + 1), w2_ = ld_rlx64(hp + 2), w3 = ld_rlx64(hp + 3);
                ok = (w0.y == tag32) && (w1_.y == tag32) && (w2_.y == tag32) && (w3.y == tag32);
                inw = make_uint4(w0.x, w1_.x, w2_.x, w3.x);
                if (++it > kSpinLimit) __trap();
            } while (!__all_sync(0xffffffffu, ok));
        } else {
            const float* op = g_oacc + ((sb * kH + slice) * kDH + sc * 2) * 2;
            const float* lp = g_lacc + (sb * kH + slice) * 32;
            float4 v[4];
            float2 lv;
            unsigned it = 0;
            if (tid == 0) STAMP(13);
            while (true) {
                float4 c[4];
#pragma unroll
                for (int i = 0; i < 4; i++) c[i] = ld_rlx_f4(op + i * 64);
                const float2 lc = ld_rlx_f2(lp);
#pragma unroll
                for (int i = 0; i < 4; i++) v[i] = ld_rlx_f4(op + i * 64);
                lv = ld_rlx_f2(lp);
                bool ok = (lc.y == cnt_full);
#pragma unroll
                for (int i = 0; i < 4; i++) ok = ok && (c[i].y == cnt_full) && (c[i].w == cnt_full);
                if (ok) break;
                if (++it > kSpinLimit) __trap();
            }
            if (tid == 0) STAMP(4);
            const float inv = __frcp_rn(lv.x);
            named_bar(1, kConsumerThreads);
#pragma unroll
            for (int i = 0; i < 4; i++) sts32(s_part + sb * kInStride + (i * 32 + sc * 2) * 2, pack_bf2(v[i].x * inv, v[i].z * inv));
            named_bar(1, kConsumerThreads);
            return;
        }
        named_bar(1, kConsumerThreads);
        sts128(s_part + sb * kInStride + sc * 16, inw);
        named_bar(1, kConsumerThreads);
    };
    uint32_t attn_left = 0, attn_next = 0;
    bool staged = false;
    auto wait_unit = [&]() {
        mbar_wait(sbase + kOffFull + slot * 32, phase);
        if (warp != 0) mbar_wait(sbase + kOffFull + slot * 32 + warp * 8, phase);
    };

#pragma unroll 1
    while (true) {
        const uint32_t tile_base = sbase + slot * kSlotBytes;
        const uint32_t aux = tile_base + kTileBytes;
        const uint32_t empty_bar = sbase + kOffEmpty + slot * 8;
        wait_unit();
        const uint32_t desc = lds32(sbase + kOffDesc + slot * 4);
        if (++slot == (uint32_t)kSlots) { slot = 0; phase ^= 1; }
        const uint32_t type = desc & 7;

        if (type == kTypeK) {
            const uint32_t pair = (desc >> 3) & 255, tile = (desc >> 11) & 31;
            uint32_t qf[16];
            bool ok = !(desc & kDescNoAux);
#pragma unroll
            for (int t = 0; t < 8; t++) {
                const uint2 a = lds64(aux + ((((2 * t) ^ g) * 4 + j) << 3));
                const uint2 b = lds64(aux + ((((2 * t + 1) ^ g) * 4 + j) << 3));
                ok = ok && (a.y == tag32) && (b.y == tag32);
                qf[2 * t] = a.x; qf[2 * t + 1] = b.x;
            }
            if (!__all_sync(0xffffffffu, ok)) {
                named_bar(1, kConsumerThreads);
                if (tid < 64) {
                    unsigned n = 0;
                    const uint2* qp = g_q + pair * 64 + tid;
                    uint2 w = ld_rlx64(qp);
                    while (w.y != tag32) {
                        w = ld_rlx64(qp);
                        if (++n > kSpinLimit) __trap();
                    }
                    sts32(aux + tid * 8, w.x);
                    asm volatile("fence.proxy.async.shared::cta;" ::: "memory");
                }
                named_bar(1, kConsumerThreads);
#pragma unroll
                for (int t = 0; t < 8; t++) {
                    qf[2 * t] = lds32(aux + ((((2 * t) ^ g) * 4 + j) << 3));
                    qf[2 * t + 1] = lds32(aux + ((((2 * t + 1) ^ g) * 4 + j) << 3));
                }
            }
            float acc[2][2][4] = {};
#pragma unroll
            for (int mt = 0; mt < 2; mt++) {
                const uint32_t a0 = tile_base + k_lane_off + mt * 4096;
#pragma unroll
                for (int t = 0; t < 8; t++) {
                    uint32_t a[4];
                    ldsm4(a, a0 ^ (t << 5));
                    mma16816(acc[mt][t & 1], a, qf[2 * t], qf[2 * t + 1]);
                }
            }
            uint32_t wv[4];
            int mo = INT_MIN;
#pragma unroll
            for (int i = 0; i < 4; i++) {
                const int mt = i >> 1, hf = i & 1;
                const float c0 = acc[mt][0][hf * 2] + acc[mt][1][hf * 2];
                const float c1 = acc[mt][0][hf * 2 + 1] + acc[mt][1][hf * 2 + 1];
                const float c = (g & 1) ? c1 : c0;
                const uint32_t bits = __float_as_uint(bfr(bfr(c) * kScale));
                wv[i] = bits | tag16;
                mo = max(mo, ord(bits));
            }
            __syncwarp();
            if (lane == 0) mbar_arrive(empty_bar);
            mo = __reduce_max_sync(0xffffffffu, diag ? mo : INT_MIN);
            if (diag) st_rlx128(g_score + pair * kSK + tile * kTileKeys + warp * 32 + g * 4, make_uint4(wv[0], wv[1], wv[2], wv[3]));
            if (tile == 0 && warp == 0) {
                const uint32_t cb = __float_as_uint(cnt_base);
                st_rlx128(reinterpret_cast<uint32_t*>(oacc + pair * (kDH * 2)) + lane * 4, make_uint4(0u, cb, 0u, cb));
                st_rlx128(reinterpret_cast<uint32_t*>(oacc + pair * (kDH * 2)) + 128 + lane * 4, make_uint4(0u, cb, 0u, cb));
                st_rlx32(reinterpret_cast<uint32_t*>(lacc + pair * 32) + lane, lane == 1 ? cb : 0u);
                asm volatile("fence.acq_rel.gpu;" ::: "memory");
            }
            if (lane == 0) st_rlx32(g_max + pair * 128 + tile * 4 + warp, ((uint32_t)ord((uint32_t)mo) & 0xffff0000u) | tag16);
        } else if (type == kTypeV) {
            const uint32_t pair = (desc >> 3) & 255, tile = (desc >> 11) & 31;
            uint4 sw = lds128(aux + (warp * 32 + g * 4) * 4);
            uint4 mw = lds128(aux + 512 + lane * 16);
            auto tags_ok = [&](const uint4& a) {
                return ((a.x & 0xffffu) == tag16) && ((a.y & 0xffffu) == tag16) && ((a.z & 0xffffu) == tag16) && ((a.w & 0xffffu) == tag16);
            };
            if (!__all_sync(0xffffffffu, tags_ok(sw) && tags_ok(mw))) {
                unsigned n = 0;
                do {
                    sw = ld_rlx128(g_score + pair * kSK + tile * kTileKeys + warp * 32 + g * 4);
                    mw = ld_rlx128(g_max + pair * 128 + lane * 4);
                    if (++n > kSpinLimit) __trap();
                } while (!__all_sync(0xffffffffu, tags_ok(sw) && tags_ok(mw)));
            }
            int mo = max(max(ord(mw.x & 0xffff0000u), ord(mw.y & 0xffff0000u)), max(ord(mw.z & 0xffff0000u), ord(mw.w & 0xffff0000u)));
            mo = __reduce_max_sync(0xffffffffu, mo);
            const float M = __uint_as_float((uint32_t)ord((uint32_t)mo));
            const uint32_t swv[4] = {sw.x, sw.y, sw.z, sw.w};
            uint32_t pb[4];
            float lsum = 0.f;
#pragma unroll
            for (int i = 0; i < 4; i++) {
                const float p = ex2((bf_hi(swv[i]) - M) * kLog2e);
                lsum += p;
                const uint32_t bits = bf_bits(p);
                pb[i] = diag ? ((g & 1) ? (bits << 16) : bits) : 0u;
            }
            lsum = diag ? lsum : 0.f;
            float acc[8][4] = {};
#pragma unroll
            for (int ks = 0; ks < 2; ks++) {
                const uint32_t a0 = tile_base + v_lane_off + ks * 4096;
#pragma unroll
                for (int t = 0; t < 8; t++) {
                    uint32_t a[4];
                    ldsm4t(a, a0 ^ (t << 5));
                    mma16816(acc[t], a, pb[2 * ks], pb[2 * ks + 1]);
                }
            }
            __syncwarp();
            if (lane == 0) mbar_arrive(empty_bar);
#pragma unroll
            for (int o = 16; o > 0; o >>= 1) lsum += __shfl_xor_sync(0xffffffffu, lsum, o);
            float U[16];
#pragma unroll
            for (int t = 0; t < 8; t++) { U[2 * t] = acc[t][0] + acc[t][3]; U[2 * t + 1] = acc[t][2] + acc[t][1]; }
            float W[8];
#pragma unroll
            for (int q = 0; q < 8; q++) {
                const int rr = (q & 1) | ((q >> 1) << 2);
                W[q] = U[rr] + __shfl_xor_sync(0xffffffffu, U[rr ^ 2], 1);
            }
            const uint32_t redb = sbase + kOffRed + rbuf * 2048 + warp * 512;
#pragma unroll
            for (int q = 0; q < 4; q++) {
                const int rr = (q & 1) | ((q >> 1) << 3);
                const int iw = (rr & 1) | ((rr >> 2) << 1);
                const int iw4 = ((rr ^ 4) & 1) | (((rr ^ 4) >> 2) << 1);
                const float X = W[iw] + __shfl_xor_sync(0xffffffffu, W[iw4], 2);
                sts_f(redb + (((rr ^ (2 * j)) * 8 + g) << 2), X);
            }
            if (lane == 0) sts_f(sbase + kOffL + rbuf * 16 + warp * 4, lsum);
            named_bar(1, kConsumerThreads);
            {
                const uint32_t rb = sbase + kOffRed + rbuf * 2048 + tid * 4;
                const float s = (lds_f(rb) + lds_f(rb + 512)) + (lds_f(rb + 1024) + lds_f(rb + 1536));
                red_add_2f32(oacc + (pair * kDH + tid) * 2, s, 1.0f);
                if (tid == 0) {
                    const uint32_t lb = sbase + kOffL + rbuf * 16;
                    red_add_2f32(lacc + pair * 32, (lds_f(lb) + lds_f(lb + 4)) + (lds_f(lb + 8) + lds_f(lb + 12)), 1.0f);
                }
            }
            rbuf ^= 1;
        } else if (type == kTypeF) {
            const uint32_t ft = desc >> 3;
            float acc[4] = {};
            const uint32_t a0 = tile_base + (warp * 128 + (mi >> 1) * 8 + r) * 32 + (((mi & 1) ^ ((r >> 2) & 1)) << 4);
            const uint32_t b0 = s_xn + g * kXnStride + (warp * 128 + 2 * j) * 2;
#pragma unroll
            for (int ks = 0; ks < 8; ks++) {
                uint32_t a[4];
                ldsm4t(a, a0 + ks * 512);
                mma16816(acc, a, lds32(b0 + ks * 32), lds32(b0 + ks * 32 + 16));
            }
            __syncwarp();
            if (lane == 0) mbar_arrive(empty_bar);
            named_bar(1, kConsumerThreads);
            const uint32_t p = s_part + (warp * 16 + g) * 32 + j * 8;
            sts_f(p, acc[0]); sts_f(p + 4, acc[1]);
            sts_f(p + 256, acc[2]); sts_f(p + 260, acc[3]);
            named_bar(1, kConsumerThreads);
            if (tid < 64) {
                const int b = tid >> 3, cp = tid & 7;
                const uint32_t bw = (ft == cta) ? b1raw : ldg_u32(b1 + ft * 16 + 2 * cp);
                float v[2];
#pragma unroll
                for (int e = 0; e < 2; e++) {
                    float s = 0.f;
#pragma unroll
                    for (int w = 0; w < 4; w++) s += lds_f(s_part + (w * 16 + 2 * cp + e) * 32 + b * 4);
                    const float hh = bfr(bfr(s) + (e ? bf_hi(bw) : bf_lo(bw)));
                    const float inner = 0.7978845608028654f * (hh + 0.044715f * hh * hh * hh);
                    v[e] = 0.5f * hh * (1.0f + tanhf(inner));
                }
                st_rlx64(g_h + b * (kF / 2) + ft * 8 + cp, pack_bf2(v[0], v[1]), tag32);
            }
        } else if (type == kTypeP) {
            const uint32_t slice = (desc >> 3) & 255, quarter = (desc >> 11) & 3;
            if (tid == 0 && staged) STAMP(8);
            if (!staged) stage_input(slice);
            staged = false;
            uint32_t bf[8][2];
#pragma unroll
            for (int ks = 0; ks < 8; ks++) {
                const uint32_t a = s_part + g * kInStride + (ks * 16 + 2 * j) * 2;
                bf[ks][0] = lds32(a);
                bf[ks][1] = lds32(a + 16);
            }
            float acc[2][2][4] = {};
            const uint32_t a0 = tile_base + warp * kPieceBytes + ((mi >> 1) * 8 + r) * 64 + (((mi & 1) ^ ((r >> 1) & 3)) << 4);
#pragma unroll
            for (int ks = 0; ks < 8; ks++) {
#pragma unroll
                for (int mt = 0; mt < 2; mt++) {
                    uint32_t a[4];
                    ldsm4t(a, (a0 + ks * 1024) ^ (mt << 5));
                    mma16816(acc[mt][ks & 1], a, bf[ks][0], bf[ks][1]);
                }
            }
            uint2* cp = g_contrib + (size_t)slice * (kB * kD) + quarter * 128 + warp * 32 + g;
#pragma unroll
            for (int mt = 0; mt < 2; mt++) {
                st_rlx64(cp + (2 * j) * kD + mt * 16, __float_as_uint(acc[mt][0][0] + acc[mt][1][0]), tag32);
                st_rlx64(cp + (2 * j + 1) * kD + mt * 16, __float_as_uint(acc[mt][0][1] + acc[mt][1][1]), tag32);
                st_rlx64(cp + (2 * j) * kD + mt * 16 + 8, __float_as_uint(acc[mt][0][2] + acc[mt][1][2]), tag32);
                st_rlx64(cp + (2 * j + 1) * kD + mt * 16 + 8, __float_as_uint(acc[mt][0][3] + acc[mt][1][3]), tag32);
            }
            __syncwarp();
            if (lane == 0) mbar_arrive(empty_bar);
            if (attn_left > 0) {
                if (--attn_left == 0) break;
                attn_next += G;
                stage_input(attn_next >> 2);
                staged = true;
            }
        } else {
            __syncwarp();
            if (lane == 0) mbar_arrive(empty_bar);
            if (tid == 0) STAMP(3);
            for (uint32_t a = cta; a < (uint32_t)kAttnUnits; a += G) attn_left++;
            if (attn_left == 0) break;
            attn_next = cta;
            stage_input(cta >> 2);
            staged = true;
            if (tid == 0) STAMP(9);

        }
    }
    if (tid == 0) STAMP(5);

#pragma unroll 1
    for (uint32_t task = cta; task < (uint32_t)kFinalTasks; task += G) {
        const int hg = lane >> 3;
        const uint32_t o = task * 32 + warp * 8 + (lane & 7);
        if (task != cta) {
            fxraw = ldg_u16(x + o);
            fb2raw = ldg_u16(b2 + (o & (kD - 1)));
        }
        const uint2* cp = g_contrib + o;
        uint2 va[8], vb[4];
#pragma unroll
        for (int i = 0; i < 8; i++) va[i] = ld_rlx64(cp + (size_t)(hg * 8 + i) * (kB * kD));
#pragma unroll
        for (int i = 0; i < 4; i++) {
            const int f = hg * 4 + i;
            vb[i] = (f < kFSlices) ? ld_rlx64(cp + (size_t)(kH + f) * (kB * kD)) : make_uint2(0u, tag32);
        }
        unsigned it = 0;
        while (true) {
            bool ok = true;
#pragma unroll
            for (int i = 0; i < 8; i++) ok = ok && (va[i].y == tag32);
#pragma unroll
            for (int i = 0; i < 4; i++) ok = ok && (vb[i].y == tag32);
            if (__all_sync(0xffffffffu, ok)) break;
#pragma unroll
            for (int i = 0; i < 8; i++)
                if (va[i].y != tag32) va[i] = ld_rlx64(cp + (size_t)(hg * 8 + i) * (kB * kD));
#pragma unroll
            for (int i = 0; i < 4; i++)
                if (vb[i].y != tag32) vb[i] = ld_rlx64(cp + (size_t)(kH + hg * 4 + i) * (kB * kD));
            if (++it > kSpinLimit) __trap();
        }
        float sa = 0.f, sb = 0.f;
#pragma unroll
        for (int i = 0; i < 8; i++) sa += __uint_as_float(va[i].x);
#pragma unroll
        for (int i = 0; i < 4; i++) sb += __uint_as_float(vb[i].x);
        sa += __shfl_xor_sync(0xffffffffu, sa, 8);
        sb += __shfl_xor_sync(0xffffffffu, sb, 8);
        sa += __shfl_xor_sync(0xffffffffu, sa, 16);
        sb += __shfl_xor_sync(0xffffffffu, sb, 16);
        if (hg == 0) {
            const float res = bfr(bf_lo(fxraw) + bfr(sa)) + bfr(bfr(sb) + bf_lo(fb2raw));
            out[o] = __float2bfloat16_rn(res);
        }
    }
}

}

typedef CUresult (*EncodeTiledFn)(CUtensorMap*, CUtensorMapDataType, cuuint32_t, void*, const cuuint64_t*, const cuuint64_t*,
                                  const cuuint32_t*, const cuuint32_t*, CUtensorMapInterleave, CUtensorMapSwizzle,
                                  CUtensorMapL2promotion, CUtensorMapFloatOOBfill);

static bool encode_weight_map(EncodeTiledFn fn, CUtensorMap* map, const void* base, int rows) {
    const cuuint64_t dims[2] = {(cuuint64_t)kD, (cuuint64_t)rows};
    const cuuint64_t strides[1] = {(cuuint64_t)kD * 2};
    const cuuint32_t box[2] = {32, 128};
    const cuuint32_t estr[2] = {1, 1};
    return fn(map, CU_TENSOR_MAP_DATA_TYPE_BFLOAT16, 2, const_cast<void*>(base), dims, strides, box, estr,
              CU_TENSOR_MAP_INTERLEAVE_NONE, CU_TENSOR_MAP_SWIZZLE_64B, CU_TENSOR_MAP_L2_PROMOTION_L2_256B,
              CU_TENSOR_MAP_FLOAT_OOB_FILL_NONE) == CUDA_SUCCESS;
}

extern "C" void kernel_launch(void* const* d_in, const int* in_sizes, int n_in, void* d_out, int out_size) {
    (void)in_sizes; (void)n_in; (void)out_size;
    const __nv_bfloat16* x  = (const __nv_bfloat16*)d_in[0];
    const __nv_bfloat16* kc = (const __nv_bfloat16*)d_in[1];
    const __nv_bfloat16* vc = (const __nv_bfloat16*)d_in[2];
    const __nv_bfloat16* wq = (const __nv_bfloat16*)d_in[3];
    const __nv_bfloat16* wo = (const __nv_bfloat16*)d_in[4];
    const __nv_bfloat16* w1 = (const __nv_bfloat16*)d_in[6];
    const __nv_bfloat16* b1 = (const __nv_bfloat16*)d_in[7];
    const __nv_bfloat16* w2 = (const __nv_bfloat16*)d_in[8];
    const __nv_bfloat16* b2 = (const __nv_bfloat16*)d_in[9];
    __nv_bfloat16* out = (__nv_bfloat16*)d_out;

    static int grid = 0;
    static EncodeTiledFn encode = nullptr;
    static CUtensorMap map_wo, map_w2;
    static const void* cached_wo = nullptr;
    static const void* cached_w2 = nullptr;
    if (grid == 0) {
        int dev = 0, sms = 0;
        cudaGetDevice(&dev);
        cudaDeviceGetAttribute(&sms, cudaDevAttrMultiProcessorCount, dev);
        cudaFuncSetAttribute(fused_decode_kernel, cudaFuncAttributeMaxDynamicSharedMemorySize, kSmemBytes);
        void* fn = nullptr;
        cudaDriverEntryPointQueryResult qres;
        cudaGetDriverEntryPoint("cuTensorMapEncodeTiled", &fn, cudaEnableDefault, &qres);
        encode = (EncodeTiledFn)fn;
        grid = sms > 0 ? (sms < kMaxGrid ? sms : kMaxGrid) : 1;
    }
    if (encode == nullptr) return;
    if (cached_wo != (const void*)wo) { encode_weight_map(encode, &map_wo, wo, kH * kDH); cached_wo = wo; }
    if (cached_w2 != (const void*)w2) { encode_weight_map(encode, &map_w2, w2, kF); cached_w2 = w2; }
    fused_decode_kernel<<<grid, kThreads, kSmemBytes>>>(x, kc, vc, wq, w1, b1, b2, out, map_wo, map_w2);
}
```
